```python
import torch

def _softmax(x, axis=-1):
    return torch.softmax(x, dim=axis)

def _gelu(x):
    return torch.nn.functional.gelu(x, approximate='tanh')

def _silu(x):
    return torch.nn.functional.silu(x)

def _sigmoid(x):
    return torch.sigmoid(x)

def _layernorm(x, axis=-1, eps=1e-05):
    m = x.mean(dim=axis, keepdim=True)
    v = x.var(dim=axis, keepdim=True, unbiased=False)
    return (x - m) / torch.sqrt(v + eps)

def _scatter_add(tgt, idx, src, axis=0):
    return tgt.clone().index_add_(axis, idx, src)

def _segment_sum(src, seg, n):
    out = torch.zeros((n,) + src.shape[1:], dtype=src.dtype)
    return out.index_add_(0, seg, src)

def _pad(x, pw):
    flat = tuple((v for pair in reversed(pw) for v in pair))
    return torch.nn.functional.pad(x, flat)
kernel_name = 'adaLN_cond__spectral_fnet__dense_activation_relu__prompt'

def setup_inputs():

    _w = lambda a: (lambda t: t.to(torch.bfloat16) if t.is_floating_point() else t)(torch.as_tensor(a))

    def _A_setup():
        B, S, D = (1, 2048, 512)
        ns = torch.arange(S)[:, None] * torch.arange(S)[None, :]
        nd = torch.arange(D)[:, None] * torch.arange(D)[None, :]
        Ws_re = torch.cos(-2.0 * torch.pi * ns / S).to(float)
        Ws_im = torch.sin(-2.0 * torch.pi * ns / S).to(float)
        Wd_re = torch.cos(-2.0 * torch.pi * nd / D).to(float)
        Wd_im = torch.sin(-2.0 * torch.pi * nd / D).to(float)
        return {'x': _w((lambda *s: torch.randn(*s, dtype=torch.bfloat16) * 0.1)(B, S, D)), 'dft_seq_re': _w(Ws_re), 'dft_seq_im': _w(Ws_im), 'dft_hid_re': _w(Wd_re), 'dft_hid_im': _w(Wd_im)}
    _A_in = _A_setup()

    def _B_setup():
        B, S, D, Dff = (1, 2048, 512, 1376)
        return {'x': _w((lambda *s: torch.randn(*s, dtype=torch.bfloat16) * 0.1)(B, S, D)), 'w1': _w((lambda *s: torch.randn(*s, dtype=torch.bfloat16) * 3.2)(D, Dff)), 'w2': _w((lambda *s: torch.randn(*s, dtype=torch.bfloat16) * 3.2)(Dff, D))}
    _B_in = _B_setup()
    return {'A_x': _A_in['x'], 'A_dft_seq_re': _A_in['dft_seq_re'], 'A_dft_seq_im': _A_in['dft_seq_im'], 'A_dft_hid_re': _A_in['dft_hid_re'], 'A_dft_hid_im': _A_in['dft_hid_im'], 'B_x': _B_in['x'], 'B_w1': _B_in['w1'], 'B_w2': _B_in['w2'], 'c': _w((lambda *s: torch.randn(*s, dtype=torch.bfloat16) * 0.2)(1, 512) * 8.0), 'w_mod': _w((lambda *s: torch.randn(*s, dtype=torch.bfloat16) * 0.2)(512, 6 * 512) * 512 ** (-0.5) * 8.0)}

def reference(A_x, A_dft_seq_re, A_dft_seq_im, A_dft_hid_re, A_dft_hid_im, B_x, B_w1, B_w2, c, w_mod):

    def _A_ref(x, dft_seq_re, dft_seq_im, dft_hid_re, dft_hid_im):
        a = torch.einsum('bsd,ed->bse', x, dft_hid_re)
        b = torch.einsum('bsd,ed->bse', x, dft_hid_im)
        y = torch.einsum('ts,bse->bte', dft_seq_re, a) - torch.einsum('ts,bse->bte', dft_seq_im, b)
        return y

    def _B_ref(x, w1, w2):
        h = torch.einsum('bsd,df->bsf', x, w1)
        zero = torch.zeros_like(h)
        h = torch.maximum(h, zero)
        return torch.einsum('bsf,fd->bsd', h, w2)
    x = A_x
    mod = (_silu(c) @ w_mod).reshape(c.shape[0], 6, 1, -1)
    sa, ca, ga, sb, cb, gb = (mod[:, 0].clone(), mod[:, 1].clone(), mod[:, 2].clone(), mod[:, 3].clone(), mod[:, 4].clone(), mod[:, 5].clone())
    h = _layernorm(x, axis=-1) * (1 + ca) + sa
    x = x + ga * _A_ref(h, A_dft_seq_re, A_dft_seq_im, A_dft_hid_re, A_dft_hid_im)
    h = _layernorm(x, axis=-1) * (1 + cb) + sb
    x = x + gb * _B_ref(h, B_w1, B_w2)
    return x
```

```cpp
#include <cuda_runtime.h>
#include <cuda_bf16.h>
#include <cuda.h>
#include <stdint.h>

namespace {

constexpr int S_ = 2048, D_ = 512, DFF_ = 1376;

__device__ __align__(1024) float          g_mod[6 * D_];
__device__ __align__(1024) __nv_bfloat16  g_ab[S_ * 2 * D_];
__device__ __align__(1024) __nv_bfloat16  g_x1[S_ * D_];
__device__ __align__(1024) __nv_bfloat16  g_h1[S_ * DFF_];

__device__ __forceinline__ uint32_t smem_u32(const void* p) { return (uint32_t)__cvta_generic_to_shared(p); }

__device__ __forceinline__ void mbar_init(uint32_t bar, uint32_t count) {
  asm volatile("mbarrier.init.shared::cta.b64 [%0], %1;" ::"r"(bar), "r"(count) : "memory");
}
__device__ __forceinline__ void mbar_expect_tx(uint32_t bar, uint32_t bytes) {
  asm volatile("mbarrier.arrive.expect_tx.shared::cta.b64 _, [%0], %1;" ::"r"(bar), "r"(bytes) : "memory");
}
__device__ __forceinline__ void mbar_arrive(uint32_t bar) {
  asm volatile("mbarrier.arrive.shared::cta.b64 _, [%0];" ::"r"(bar) : "memory");
}
__device__ __forceinline__ bool mbar_try_wait(uint32_t bar, uint32_t parity) {
  uint32_t ok;
  asm volatile(
      "{\n.reg .pred p;\n"
      "mbarrier.try_wait.parity.shared::cta.b64 p, [%1], %2;\n"
      "selp.u32 %0, 1, 0, p;\n}\n"
      : "=r"(ok)
      : "r"(bar), "r"(parity)
      : "memory");
  return ok != 0;
}
__device__ __forceinline__ void mbar_wait(uint32_t bar, uint32_t parity) {
  uint32_t spins = 0;
  while (!mbar_try_wait(bar, parity)) {
    if (++spins > (1u << 24)) __trap();
  }
}
__device__ __forceinline__ void tma_load_2d(uint32_t dst, const CUtensorMap* map, int c0, int c1, uint32_t bar) {
  asm volatile(
      "cp.async.bulk.tensor.2d.shared::cluster.global.mbarrier::complete_tx::bytes [%0], [%1, {%3, %4}], [%2];"
      ::"r"(dst), "l"(map), "r"(bar), "r"(c0), "r"(c1)
      : "memory");
}
__device__ __forceinline__ void prefetch_tmap(const CUtensorMap* map) {
  asm volatile("prefetch.tensormap [%0];" ::"l"(map) : "memory");
}
__device__ __forceinline__ void wgmma_fence() { asm volatile("wgmma.fence.sync.aligned;" ::: "memory"); }
__device__ __forceinline__ void wgmma_commit() { asm volatile("wgmma.commit_group.sync.aligned;" ::: "memory"); }
template <int N>
__device__ __forceinline__ void wgmma_wait() { asm volatile("wgmma.wait_group.sync.aligned %0;" ::"n"(N) : "memory"); }
__device__ __forceinline__ void fence_proxy_async() { asm volatile("fence.proxy.async.shared::cta;" ::: "memory"); }
__device__ __forceinline__ void named_bar_sync(int id, int nthreads) {
  asm volatile("bar.sync %0, %1;" ::"r"(id), "r"(nthreads) : "memory");
}
__device__ __forceinline__ void griddep_wait() { asm volatile("griddepcontrol.wait;" ::: "memory"); }
__device__ __forceinline__ void griddep_launch() { asm volatile("griddepcontrol.launch_dependents;" ::: "memory"); }
__device__ __forceinline__ void cluster_sync_all() {
  asm volatile("barrier.cluster.arrive.release.aligned;\nbarrier.cluster.wait.acquire.aligned;" ::: "memory");
}
__device__ __forceinline__ uint32_t cluster_ctarank() {
  uint32_t r;
  asm volatile("mov.u32 %0, %%cluster_ctarank;" : "=r"(r));
  return r;
}

__device__ __forceinline__ uint64_t desc_sw128(uint32_t addr, uint32_t lbo_bytes, uint32_t sbo_bytes) {
  uint64_t d = 0;
  d |= (uint64_t)((addr & 0x3FFFF) >> 4);
  d |= (uint64_t)((lbo_bytes & 0x3FFFF) >> 4) << 16;
  d |= (uint64_t)((sbo_bytes & 0x3FFFF) >> 4) << 32;
  d |= (uint64_t)1 << 62;
  return d;
}

template <int TNSPB, int SCALEA>
__device__ __forceinline__ void wgmma_n128(float (&d)[64], uint64_t da, uint64_t db, int scaleD) {
  asm volatile("{\n.reg .pred p;\nsetp.ne.b32 p, %66, 0;\n"
    "wgmma.mma_async.sync.aligned.m64n128k16.f32.bf16.bf16 {%0, %1, %2, %3, %4, %5, %6, %7, %8, %9, %10, %11, %12, %13, %14, %15, %16, %17, %18, %19, %20, %21, %22, %23, %24, %25, %26, %27, %28, %29, %30, %31, %32, %33, %34, %35, %36, %37, %38, %39, %40, %41, %42, %43, %44, %45, %46, %47, %48, %49, %50, %51, %52, %53, %54, %55, %56, %57, %58, %59, %60, %61, %62, %63}, %64, %65, p, %68, 1, 0, %67;\n}\n"
    : "+f"(d[0]), "+f"(d[1]), "+f"(d[2]), "+f"(d[3]), "+f"(d[4]), "+f"(d[5]), "+f"(d[6]), "+f"(d[7]), "+f"(d[8]), "+f"(d[9]), "+f"(d[10]), "+f"(d[11]), "+f"(d[12]), "+f"(d[13]), "+f"(d[14]), "+f"(d[15]), "+f"(d[16]), "+f"(d[17]), "+f"(d[18]), "+f"(d[19]), "+f"(d[20]), "+f"(d[21]), "+f"(d[22]), "+f"(d[23]), "+f"(d[24]), "+f"(d[25]), "+f"(d[26]), "+f"(d[27]), "+f"(d[28]), "+f"(d[29]), "+f"(d[30]), "+f"(d[31]), "+f"(d[32]), "+f"(d[33]), "+f"(d[34]), "+f"(d[35]), "+f"(d[36]), "+f"(d[37]), "+f"(d[38]), "+f"(d[39]), "+f"(d[40]), "+f"(d[41]), "+f"(d[42]), "+f"(d[43]), "+f"(d[44]), "+f"(d[45]), "+f"(d[46]), "+f"(d[47]), "+f"(d[48]), "+f"(d[49]), "+f"(d[50]), "+f"(d[51]), "+f"(d[52]), "+f"(d[53]), "+f"(d[54]), "+f"(d[55]), "+f"(d[56]), "+f"(d[57]), "+f"(d[58]), "+f"(d[59]), "+f"(d[60]), "+f"(d[61]), "+f"(d[62]), "+f"(d[63])
    : "l"(da), "l"(db), "r"(scaleD), "n"(TNSPB), "n"(SCALEA));
}

template <int TNSPB, int SCALEA>
__device__ __forceinline__ void wgmma_n176(float (&d)[88], uint64_t da, uint64_t db, int scaleD) {
  asm volatile("{\n.reg .pred p;\nsetp.ne.b32 p, %90, 0;\n"
    "wgmma.mma_async.sync.aligned.m64n176k16.f32.bf16.bf16 {%0, %1, %2, %3, %4, %5, %6, %7, %8, %9, %10, %11, %12, %13, %14, %15, %16, %17, %18, %19, %20, %21, %22, %23, %24, %25, %26, %27, %28, %29, %30, %31, %32, %33, %34, %35, %36, %37, %38, %39, %40, %41, %42, %43, %44, %45, %46, %47, %48, %49, %50, %51, %52, %53, %54, %55, %56, %57, %58, %59, %60, %61, %62, %63, %64, %65, %66, %67, %68, %69, %70, %71, %72, %73, %74, %75, %76, %77, %78, %79, %80, %81, %82, %83, %84, %85, %86, %87}, %88, %89, p, %92, 1, 0, %91;\n}\n"
    : "+f"(d[0]), "+f"(d[1]), "+f"(d[2]), "+f"(d[3]), "+f"(d[4]), "+f"(d[5]), "+f"(d[6]), "+f"(d[7]), "+f"(d[8]), "+f"(d[9]), "+f"(d[10]), "+f"(d[11]), "+f"(d[12]), "+f"(d[13]), "+f"(d[14]), "+f"(d[15]), "+f"(d[16]), "+f"(d[17]), "+f"(d[18]), "+f"(d[19]), "+f"(d[20]), "+f"(d[21]), "+f"(d[22]), "+f"(d[23]), "+f"(d[24]), "+f"(d[25]), "+f"(d[26]), "+f"(d[27]), "+f"(d[28]), "+f"(d[29]), "+f"(d[30]), "+f"(d[31]), "+f"(d[32]), "+f"(d[33]), "+f"(d[34]), "+f"(d[35]), "+f"(d[36]), "+f"(d[37]), "+f"(d[38]), "+f"(d[39]), "+f"(d[40]), "+f"(d[41]), "+f"(d[42]), "+f"(d[43]), "+f"(d[44]), "+f"(d[45]), "+f"(d[46]), "+f"(d[47]), "+f"(d[48]), "+f"(d[49]), "+f"(d[50]), "+f"(d[51]), "+f"(d[52]), "+f"(d[53]), "+f"(d[54]), "+f"(d[55]), "+f"(d[56]), "+f"(d[57]), "+f"(d[58]), "+f"(d[59]), "+f"(d[60]), "+f"(d[61]), "+f"(d[62]), "+f"(d[63]), "+f"(d[64]), "+f"(d[65]), "+f"(d[66]), "+f"(d[67]), "+f"(d[68]), "+f"(d[69]), "+f"(d[70]), "+f"(d[71]), "+f"(d[72]), "+f"(d[73]), "+f"(d[74]), "+f"(d[75]), "+f"(d[76]), "+f"(d[77]), "+f"(d[78]), "+f"(d[79]), "+f"(d[80]), "+f"(d[81]), "+f"(d[82]), "+f"(d[83]), "+f"(d[84]), "+f"(d[85]), "+f"(d[86]), "+f"(d[87])
    : "l"(da), "l"(db), "r"(scaleD), "n"(TNSPB), "n"(SCALEA));
}


__device__ __forceinline__ float bf16_round(float v) { return __bfloat162float(__float2bfloat16(v)); }
__device__ __forceinline__ uint32_t pack_bf16(float lo, float hi) {
  __nv_bfloat162 t = __floats2bfloat162_rn(lo, hi);
  return *reinterpret_cast<uint32_t*>(&t);
}
__device__ __forceinline__ float2 unpack_bf16(uint32_t u) {
  __nv_bfloat162 t = *reinterpret_cast<__nv_bfloat162*>(&u);
  return __bfloat1622float2(t);
}
__device__ __forceinline__ float warp_sum(float v) {
#pragma unroll
  for (int o = 16; o > 0; o >>= 1) v += __shfl_xor_sync(0xffffffffu, v, o);
  return v;
}

__global__ void __launch_bounds__(256) k_mod(const __nv_bfloat16* __restrict__ c, const __nv_bfloat16* __restrict__ w_mod) {
  __shared__ float red[32][65];
  __shared__ float sc[D_];
  griddep_launch();
  for (int i = threadIdx.x; i < D_; i += 256) {
    float v = __bfloat162float(c[i]);
    sc[i] = bf16_round(v / (1.0f + __expf(-v)));
  }
  __syncthreads();
  const int tx = threadIdx.x & 7, ty = threadIdx.x >> 3;
  const int col = blockIdx.x * 64 + tx * 8;
  float acc[8];
#pragma unroll
  for (int j = 0; j < 8; j++) acc[j] = 0.f;
  uint4 v[16];
#pragma unroll
  for (int r = 0; r < 16; r++) v[r] = __ldg(reinterpret_cast<const uint4*>(w_mod + (size_t)(ty * 16 + r) * (6 * D_) + col));
#pragma unroll
  for (int r = 0; r < 16; r++) {
    float s = sc[ty * 16 + r];
    const uint32_t* u = reinterpret_cast<const uint32_t*>(&v[r]);
#pragma unroll
    for (int j = 0; j < 4; j++) {
      float2 f = unpack_bf16(u[j]);
      acc[2 * j] += s * f.x;
      acc[2 * j + 1] += s * f.y;
    }
  }
#pragma unroll
  for (int j = 0; j < 8; j++) red[ty][tx * 8 + j] = acc[j];
  __syncthreads();
  if (threadIdx.x < 64) {
    float s = 0.f;
#pragma unroll
    for (int r = 0; r < 32; r++) s += red[r][threadIdx.x];
    g_mod[blockIdx.x * 64 + threadIdx.x] = bf16_round(s);
  }
}

template <int MODE>
struct LnCfg;
template <>
struct LnCfg<0> { static constexpr int BN = 128, STAGE_BYTES = 16384, STAGES = 4, LDO = 1024, NTOT = 1024; };
template <>
struct LnCfg<1> { static constexpr int BN = 176, STAGE_BYTES = 24576, STAGES = 3, LDO = DFF_, NTOT = DFF_; };

constexpr int LN_A_BYTES = 128 * 512 * 2;

template <int MODE>
__global__ void __launch_bounds__(384, 1)
k_ln_gemm(const __grid_constant__ CUtensorMap mapB0, const __grid_constant__ CUtensorMap mapB1,
          const __nv_bfloat16* __restrict__ xin, __nv_bfloat16* __restrict__ out) {
  using C = LnCfg<MODE>;
  constexpr int BN = C::BN, STAGES = C::STAGES, KT = 8;
  extern __shared__ __align__(1024) uint8_t smem[];
  uint8_t* sA = smem;
  uint8_t* sB = smem + LN_A_BYTES;
  uint64_t* bars = reinterpret_cast<uint64_t*>(smem + LN_A_BYTES + STAGES * C::STAGE_BYTES);
  const uint32_t full0 = smem_u32(bars), empty0 = smem_u32(bars + STAGES);

  const int tid = threadIdx.x, warp = tid >> 5, lane = tid & 31;
  const int m0 = blockIdx.y * 128, n0 = blockIdx.x * BN;
  const CUtensorMap* mapB = &mapB0;
  int nb = n0;
  if (MODE == 0 && n0 >= 512) { mapB = &mapB1; nb = n0 - 512; }

  if (tid == 0) {
    for (int s = 0; s < STAGES; s++) { mbar_init(full0 + 8 * s, 1); mbar_init(empty0 + 8 * s, 8); }
    asm volatile("fence.mbarrier_init.release.cluster;" ::: "memory");
    fence_proxy_async();
  }
  __syncthreads();

  auto issue_b = [&](int kt, int s) {
    const uint32_t bar = full0 + 8 * s;
    const uint32_t dst = smem_u32(sB + s * C::STAGE_BYTES);
    mbar_expect_tx(bar, C::STAGE_BYTES);
    if (MODE == 0) {
      tma_load_2d(dst, mapB, kt * 64, nb, bar);
    } else {
#pragma unroll
      for (int j = 0; j < 3; j++) tma_load_2d(dst + j * 8192, mapB, nb + j * 64, kt * 64, bar);
    }
  };
  if (tid == 0) {
    for (int s = 0; s < STAGES; s++) issue_b(s, s);
  }

  griddep_wait();
  griddep_launch();

  {
    const float* scl = g_mod + (MODE == 0 ? 1 : 4) * D_;
    const float* sft = g_mod + (MODE == 0 ? 0 : 3) * D_;
    float sc[16], sh[16];
#pragma unroll
    for (int h = 0; h < 2; h++)
#pragma unroll
      for (int j = 0; j < 8; j++) {
        const int col = h * 256 + lane * 8 + j;
        sc[h * 8 + j] = bf16_round(1.0f + scl[col]);
        sh[h * 8 + j] = sft[col];
      }
    for (int row = warp; row < 128; row += 12) {
      const uint4* src = reinterpret_cast<const uint4*>(xin + (size_t)(m0 + row) * D_);
      uint4 v0 = src[lane], v1 = src[lane + 32];
      float f[16];
      {
        const uint32_t* u0 = reinterpret_cast<const uint32_t*>(&v0);
        const uint32_t* u1 = reinterpret_cast<const uint32_t*>(&v1);
#pragma unroll
        for (int j = 0; j < 4; j++) {
          float2 a = unpack_bf16(u0[j]), b = unpack_bf16(u1[j]);
          f[2 * j] = a.x; f[2 * j + 1] = a.y; f[8 + 2 * j] = b.x; f[8 + 2 * j + 1] = b.y;
        }
      }
      float s = 0.f;
#pragma unroll
      for (int j = 0; j < 16; j++) s += f[j];
      const float mean = warp_sum(s) * (1.0f / D_);
      float q = 0.f;
#pragma unroll
      for (int j = 0; j < 16; j++) { float d = f[j] - mean; q += d * d; }
      const float rstd = rsqrtf(warp_sum(q) * (1.0f / D_) + 1e-5f);
      uint4 o0, o1;
      uint32_t* p0 = reinterpret_cast<uint32_t*>(&o0);
      uint32_t* p1 = reinterpret_cast<uint32_t*>(&o1);
#pragma unroll
      for (int j = 0; j < 4; j++) {
        p0[j] = pack_bf16((f[2 * j] - mean) * rstd * sc[2 * j] + sh[2 * j], (f[2 * j + 1] - mean) * rstd * sc[2 * j + 1] + sh[2 * j + 1]);
        p1[j] = pack_bf16((f[8 + 2 * j] - mean) * rstd * sc[8 + 2 * j] + sh[8 + 2 * j],
                          (f[8 + 2 * j + 1] - mean) * rstd * sc[8 + 2 * j + 1] + sh[8 + 2 * j + 1]);
      }
      const int c0 = lane, c1 = lane + 32;
      *reinterpret_cast<uint4*>(sA + (c0 >> 3) * 16384 + row * 128 + (((c0 & 7) ^ (row & 7)) << 4)) = o0;
      *reinterpret_cast<uint4*>(sA + (c1 >> 3) * 16384 + row * 128 + (((c1 & 7) ^ (row & 7)) << 4)) = o1;
    }
  }
  fence_proxy_async();
  __syncthreads();

  if (warp < 4) {
    if (tid == 0) {
      for (int kt = STAGES; kt < KT; kt++) {
        const int s = kt % STAGES;
        mbar_wait(empty0 + 8 * s, ((kt / STAGES) - 1) & 1);
        issue_b(kt, s);
      }
    }
  } else {
    const int wg = (warp >> 2) - 1;
    float acc[BN / 2];
#pragma unroll
    for (int i = 0; i < BN / 2; i++) acc[i] = 0.f;
    const uint32_t a_base = smem_u32(sA) + wg * 8192;
    for (int kt = 0; kt < KT; kt++) {
      const int s = kt % STAGES;
      mbar_wait(full0 + 8 * s, (kt / STAGES) & 1);
      wgmma_fence();
      const uint32_t bs = smem_u32(sB + s * C::STAGE_BYTES);
#pragma unroll
      for (int k = 0; k < 4; k++) {
        const uint64_t da = desc_sw128(a_base + kt * 16384 + k * 32, 16, 1024);
        if (MODE == 0) {
          const uint64_t db = desc_sw128(bs + k * 32, 16, 1024);
          wgmma_n128<0, 1>(*reinterpret_cast<float(*)[64]>(acc), da, db, 1);
        } else {
          const uint64_t db = desc_sw128(bs + k * 2048, 8192, 1024);
          wgmma_n176<1, 1>(*reinterpret_cast<float(*)[88]>(acc), da, db, 1);
        }
      }
      wgmma_commit();
      wgmma_wait<1>();
      if (kt > 0 && lane == 0) mbar_arrive(empty0 + 8 * ((kt - 1) % STAGES));
    }
    wgmma_wait<0>();
    named_bar_sync(1, 256);
    constexpr int LDS = BN * 2 + 16;
    uint8_t* st = sA + (warp - 4) * (16 * LDS);
    {
      const int r = lane >> 2, cq = (lane & 3) * 2;
#pragma unroll
      for (int j = 0; j < BN / 8; j++) {
        float v0 = acc[4 * j], v1 = acc[4 * j + 1], v2 = acc[4 * j + 2], v3 = acc[4 * j + 3];
        if (MODE == 1) { v0 = fmaxf(v0, 0.f); v1 = fmaxf(v1, 0.f); v2 = fmaxf(v2, 0.f); v3 = fmaxf(v3, 0.f); }
        *reinterpret_cast<uint32_t*>(st + r * LDS + (j * 8 + cq) * 2) = pack_bf16(v0, v1);
        *reinterpret_cast<uint32_t*>(st + (r + 8) * LDS + (j * 8 + cq) * 2) = pack_bf16(v2, v3);
      }
    }
    __syncwarp();
    constexpr int CH = BN / 8;
    const int mrow = m0 + wg * 64 + (warp & 3) * 16;
    for (int idx = lane; idx < 16 * CH; idx += 32) {
      const int r = idx / CH, ch = idx % CH;
      if (n0 + ch * 8 < C::NTOT) {
        uint4 v = *reinterpret_cast<const uint4*>(st + r * LDS + ch * 16);
        *reinterpret_cast<uint4*>(out + (size_t)(mrow + r) * C::LDO + n0 + ch * 8) = v;
      }
    }
  }
}

constexpr int SK_STAGES = 4;
constexpr int SK_STAGE_BYTES = 32768;
constexpr int SK_XCH_BYTES = 32768;

template <int MODE>
__global__ void __cluster_dims__(2, 1, 1) __launch_bounds__(384, 1)
k_sk_gemm(const __grid_constant__ CUtensorMap mapA0, const __grid_constant__ CUtensorMap mapA1,
          const __grid_constant__ CUtensorMap mapB, const __nv_bfloat16* __restrict__ res,
          __nv_bfloat16* __restrict__ out) {
  constexpr int KT = (MODE == 0) ? 32 : 11;
  extern __shared__ __align__(1024) uint8_t smem[];
  uint8_t* sStage = smem;
  uint8_t* sX = smem + SK_STAGES * SK_STAGE_BYTES;
  uint64_t* bars = reinterpret_cast<uint64_t*>(smem + SK_STAGES * SK_STAGE_BYTES + SK_XCH_BYTES);
  const uint32_t full0 = smem_u32(bars), empty0 = smem_u32(bars + SK_STAGES);

  const int tid = threadIdx.x, warp = tid >> 5, lane = tid & 31;
  const int half = blockIdx.x & 1;
  const int m0 = blockIdx.y * 128, n0 = (blockIdx.x >> 1) * 128;

  if (tid == 0) {
    for (int s = 0; s < SK_STAGES; s++) { mbar_init(full0 + 8 * s, 1); mbar_init(empty0 + 8 * s, 8); }
    asm volatile("fence.mbarrier_init.release.cluster;" ::: "memory");
    fence_proxy_async();
  }
  __syncthreads();
  griddep_wait();
  griddep_launch();

  if (warp < 4) {
    if (tid == 0) {
      const CUtensorMap* mapA = (MODE == 0 && half) ? &mapA1 : &mapA0;
      const int kbase = (MODE == 0) ? 0 : half * 11 * 64;
      const int nb = (MODE == 0) ? n0 + half * 512 : n0;
      for (int kt = 0; kt < KT; kt++) {
        const int s = kt % SK_STAGES;
        if (kt >= SK_STAGES) mbar_wait(empty0 + 8 * s, ((kt / SK_STAGES) - 1) & 1);
        const uint32_t bar = full0 + 8 * s;
        const uint32_t dst = smem_u32(sStage + s * SK_STAGE_BYTES);
        mbar_expect_tx(bar, SK_STAGE_BYTES);
        tma_load_2d(dst, mapA, kbase + kt * 64, m0, bar);
        tma_load_2d(dst + 16384, &mapB, nb, kbase + kt * 64, bar);
        tma_load_2d(dst + 16384 + 8192, &mapB, nb + 64, kbase + kt * 64, bar);
      }
    }
    cluster_sync_all();
  } else {
    const int wg = (warp >> 2) - 1;
    float acc[64];
#pragma unroll
    for (int i = 0; i < 64; i++) acc[i] = 0.f;
    for (int kt = 0; kt < KT; kt++) {
      const int s = kt % SK_STAGES;
      mbar_wait(full0 + 8 * s, (kt / SK_STAGES) & 1);
      wgmma_fence();
      const uint32_t as = smem_u32(sStage + s * SK_STAGE_BYTES) + wg * 8192;
      const uint32_t bs = smem_u32(sStage + s * SK_STAGE_BYTES) + 16384;
#pragma unroll
      for (int k = 0; k < 4; k++) {
        const uint64_t da = desc_sw128(as + k * 32, 16, 1024);
        const uint64_t db = desc_sw128(bs + k * 2048, 8192, 1024);
        wgmma_n128<1, 1>(acc, da, db, 1);
      }
      wgmma_commit();
      wgmma_wait<1>();
      if (kt > 0 && lane == 0) mbar_arrive(empty0 + 8 * ((kt - 1) % SK_STAGES));
    }
    wgmma_wait<0>();
    const int t = tid & 127;
    if (wg != half) {
      uint32_t remote;
      asm volatile("mapa.shared::cluster.u32 %0, %1, %2;" : "=r"(remote) : "r"(smem_u32(sX)), "r"(half ^ 1));
#pragma unroll
      for (int i = 0; i < 16; i++) {
        asm volatile("st.shared::cluster.v4.f32 [%0], {%1, %2, %3, %4};" ::"r"(remote + (i * 128 + t) * 16), "f"(acc[4 * i]),
                     "f"(acc[4 * i + 1]), "f"(acc[4 * i + 2]), "f"(acc[4 * i + 3])
                     : "memory");
      }
    }
    cluster_sync_all();
    if (wg == half) {
      const float* gate = g_mod + (MODE == 0 ? 2 : 5) * D_;
      const int r = lane >> 2, cq = (lane & 3) * 2;
      const int row0 = m0 + wg * 64 + (warp & 3) * 16 + r;
#pragma unroll
      for (int j = 0; j < 16; j++) {
        const float4 o = *reinterpret_cast<const float4*>(sX + (j * 128 + t) * 16);
        float v0, v1, v2, v3;
        if (MODE == 0) {
          if (half == 0) { v0 = acc[4 * j] - o.x; v1 = acc[4 * j + 1] - o.y; v2 = acc[4 * j + 2] - o.z; v3 = acc[4 * j + 3] - o.w; }
          else { v0 = o.x - acc[4 * j]; v1 = o.y - acc[4 * j + 1]; v2 = o.z - acc[4 * j + 2]; v3 = o.w - acc[4 * j + 3]; }
        } else {
          v0 = acc[4 * j] + o.x; v1 = acc[4 * j + 1] + o.y; v2 = acc[4 * j + 2] + o.z; v3 = acc[4 * j + 3] + o.w;
        }
        const int col = n0 + j * 8 + cq;
        const float g0 = gate[col], g1 = gate[col + 1];
        const float2 r0 = unpack_bf16(*reinterpret_cast<const uint32_t*>(res + (size_t)row0 * D_ + col));
        const float2 r1 = unpack_bf16(*reinterpret_cast<const uint32_t*>(res + (size_t)(row0 + 8) * D_ + col));
        *reinterpret_cast<uint32_t*>(out + (size_t)row0 * D_ + col) = pack_bf16(r0.x + g0 * v0, r0.y + g1 * v1);
        *reinterpret_cast<uint32_t*>(out + (size_t)(row0 + 8) * D_ + col) = pack_bf16(r1.x + g0 * v2, r1.y + g1 * v3);
      }
    }
  }
}

typedef CUresult (*PFN_encodeTiled_t)(CUtensorMap*, CUtensorMapDataType, cuuint32_t, void*, const cuuint64_t*,
                                      const cuuint64_t*, const cuuint32_t*, const cuuint32_t*, CUtensorMapInterleave,
                                      CUtensorMapSwizzle, CUtensorMapL2promotion, CUtensorMapFloatOOBfill);

CUtensorMap make_map(PFN_encodeTiled_t enc, const void* ptr, uint64_t inner, uint64_t outer, uint32_t box_inner,
                     uint32_t box_outer) {
  CUtensorMap m;
  cuuint64_t dims[2] = {inner, outer};
  cuuint64_t strides[1] = {inner * 2};
  cuuint32_t box[2] = {box_inner, box_outer};
  cuuint32_t es[2] = {1, 1};
  enc(&m, CU_TENSOR_MAP_DATA_TYPE_BFLOAT16, 2, const_cast<void*>(ptr), dims, strides, box, es,
      CU_TENSOR_MAP_INTERLEAVE_NONE, CU_TENSOR_MAP_SWIZZLE_128B, CU_TENSOR_MAP_L2_PROMOTION_L2_256B,
      CU_TENSOR_MAP_FLOAT_OOB_FILL_NONE);
  return m;
}

template <typename... KArgs, typename... Args>
void launch(void (*kern)(KArgs...), dim3 grid, dim3 block, size_t smem, bool pdl, Args... args) {
  cudaLaunchConfig_t cfg = {};
  cfg.gridDim = grid;
  cfg.blockDim = block;
  cfg.dynamicSmemBytes = smem;
  cfg.stream = cudaStreamPerThread;
  cudaLaunchAttribute at[1];
  at[0].id = cudaLaunchAttributeProgrammaticStreamSerialization;
  at[0].val.programmaticStreamSerializationAllowed = 1;
  cfg.attrs = at;
  cfg.numAttrs = pdl ? 1 : 0;
  cudaLaunchKernelEx(&cfg, kern, KArgs(args)...);
}

}

extern "C" void kernel_launch(void* const* d_in, const int* in_sizes, int n_in, void* d_out, int out_size) {
  const __nv_bfloat16* x = (const __nv_bfloat16*)d_in[0];
  const __nv_bfloat16* ws_re = (const __nv_bfloat16*)d_in[1];
  const __nv_bfloat16* ws_im = (const __nv_bfloat16*)d_in[2];
  const __nv_bfloat16* wd_re = (const __nv_bfloat16*)d_in[3];
  const __nv_bfloat16* wd_im = (const __nv_bfloat16*)d_in[4];
  const __nv_bfloat16* w1 = (const __nv_bfloat16*)d_in[6];
  const __nv_bfloat16* w2 = (const __nv_bfloat16*)d_in[7];
  const __nv_bfloat16* c = (const __nv_bfloat16*)d_in[8];
  const __nv_bfloat16* w_mod = (const __nv_bfloat16*)d_in[9];
  __nv_bfloat16* out = (__nv_bfloat16*)d_out;

  void* fn = nullptr;
  cudaDriverEntryPointQueryResult qres;
  cudaGetDriverEntryPoint("cuTensorMapEncodeTiled", &fn, cudaEnableDefault, &qres);
  PFN_encodeTiled_t enc = (PFN_encodeTiled_t)fn;

  void *p_ab, *p_x1, *p_h1;
  cudaGetSymbolAddress(&p_ab, g_ab);
  cudaGetSymbolAddress(&p_x1, g_x1);
  cudaGetSymbolAddress(&p_h1, g_h1);

  const CUtensorMap m_wd_re = make_map(enc, wd_re, D_, D_, 64, 128);
  const CUtensorMap m_wd_im = make_map(enc, wd_im, D_, D_, 64, 128);
  const CUtensorMap m_ws_re = make_map(enc, ws_re, S_, S_, 64, 128);
  const CUtensorMap m_ws_im = make_map(enc, ws_im, S_, S_, 64, 128);
  const CUtensorMap m_ab = make_map(enc, p_ab, 2 * D_, S_, 64, 64);
  const CUtensorMap m_w1 = make_map(enc, w1, DFF_, D_, 64, 64);
  const CUtensorMap m_h1 = make_map(enc, p_h1, DFF_, S_, 64, 128);
  const CUtensorMap m_w2 = make_map(enc, w2, D_, DFF_, 64, 64);

  constexpr int SM_K1 = LN_A_BYTES + LnCfg<0>::STAGES * LnCfg<0>::STAGE_BYTES + 256;
  constexpr int SM_K3 = LN_A_BYTES + LnCfg<1>::STAGES * LnCfg<1>::STAGE_BYTES + 256;
  constexpr int SM_SK = SK_STAGES * SK_STAGE_BYTES + SK_XCH_BYTES + 256;
  cudaFuncSetAttribute(k_ln_gemm<0>, cudaFuncAttributeMaxDynamicSharedMemorySize, SM_K1);
  cudaFuncSetAttribute(k_ln_gemm<1>, cudaFuncAttributeMaxDynamicSharedMemorySize, SM_K3);
  cudaFuncSetAttribute(k_sk_gemm<0>, cudaFuncAttributeMaxDynamicSharedMemorySize, SM_SK);
  cudaFuncSetAttribute(k_sk_gemm<1>, cudaFuncAttributeMaxDynamicSharedMemorySize, SM_SK);

  launch(k_mod, dim3(48), dim3(256), 0, false, c, w_mod);
  launch(k_ln_gemm<0>, dim3(8, 16), dim3(384), SM_K1, true, m_wd_re, m_wd_im, x, (__nv_bfloat16*)p_ab);
  launch(k_sk_gemm<0>, dim3(8, 16), dim3(384), SM_SK, true, m_ws_re, m_ws_im, m_ab, x, (__nv_bfloat16*)p_x1);
  launch(k_ln_gemm<1>, dim3(8, 16), dim3(384), SM_K3, true, m_w1, m_w1, (const __nv_bfloat16*)p_x1, (__nv_bfloat16*)p_h1);
  launch(k_sk_gemm<1>, dim3(8, 16), dim3(384), SM_SK, true, m_h1, m_h1, m_w2, (const __nv_bfloat16*)p_x1, out);
}
```

```cpp
#include <cuda_runtime.h>
#include <cuda_bf16.h>
#include <cuda.h>
#include <stdint.h>

namespace {

constexpr int S_ = 2048, D_ = 512, DFF_ = 1376;

__device__ __align__(1024) float          g_mod[6 * D_];
__device__ __align__(1024) __nv_bfloat16  g_ab[S_ * 2 * D_];
__device__ __align__(1024) __nv_bfloat16  g_x1[S_ * D_];
__device__ __align__(1024) __nv_bfloat16  g_h1[S_ * DFF_];

#define TL(slot, which, cond)

__device__ __forceinline__ uint32_t smem_u32(const void* p) { return (uint32_t)__cvta_generic_to_shared(p); }

__device__ __forceinline__ void mbar_init(uint32_t bar, uint32_t count) {
  asm volatile("mbarrier.init.shared::cta.b64 [%0], %1;" ::"r"(bar), "r"(count) : "memory");
}
__device__ __forceinline__ void mbar_expect_tx(uint32_t bar, uint32_t bytes) {
  asm volatile("mbarrier.arrive.expect_tx.shared::cta.b64 _, [%0], %1;" ::"r"(bar), "r"(bytes) : "memory");
}
__device__ __forceinline__ void mbar_arrive(uint32_t bar) {
  asm volatile("mbarrier.arrive.shared::cta.b64 _, [%0];" ::"r"(bar) : "memory");
}
__device__ __forceinline__ bool mbar_try_wait(uint32_t bar, uint32_t parity) {
  uint32_t ok;
  asm volatile(
      "{\n.reg .pred p;\n"
      "mbarrier.try_wait.parity.shared::cta.b64 p, [%1], %2;\n"
      "selp.u32 %0, 1, 0, p;\n}\n"
      : "=r"(ok)
      : "r"(bar), "r"(parity)
      : "memory");
  return ok != 0;
}
__device__ __forceinline__ void mbar_wait(uint32_t bar, uint32_t parity) {
  uint32_t spins = 0;
  while (!mbar_try_wait(bar, parity)) {
    if (++spins > (1u << 24)) __trap();
  }
}
__device__ __forceinline__ void tma_load_2d(uint32_t dst, const CUtensorMap* map, int c0, int c1, uint32_t bar) {
  asm volatile(
      "cp.async.bulk.tensor.2d.shared::cluster.global.mbarrier::complete_tx::bytes [%0], [%1, {%3, %4}], [%2];"
      ::"r"(dst), "l"(map), "r"(bar), "r"(c0), "r"(c1)
      : "memory");
}
__device__ __forceinline__ void prefetch_tmap(const CUtensorMap* map) {
  asm volatile("prefetch.tensormap [%0];" ::"l"(map) : "memory");
}
__device__ __forceinline__ void wgmma_fence() { asm volatile("wgmma.fence.sync.aligned;" ::: "memory"); }
__device__ __forceinline__ void wgmma_commit() { asm volatile("wgmma.commit_group.sync.aligned;" ::: "memory"); }
template <int N>
__device__ __forceinline__ void wgmma_wait() { asm volatile("wgmma.wait_group.sync.aligned %0;" ::"n"(N) : "memory"); }
__device__ __forceinline__ void fence_proxy_async() { asm volatile("fence.proxy.async.shared::cta;" ::: "memory"); }
__device__ __forceinline__ void named_bar_sync(int id, int nthreads) {
  asm volatile("bar.sync %0, %1;" ::"r"(id), "r"(nthreads) : "memory");
}
__device__ __forceinline__ void griddep_wait() { asm volatile("griddepcontrol.wait;" ::: "memory"); }
__device__ __forceinline__ void griddep_launch() { asm volatile("griddepcontrol.launch_dependents;" ::: "memory"); }
__device__ __forceinline__ void cluster_sync_all() {
  asm volatile("barrier.cluster.arrive.release.aligned;\nbarrier.cluster.wait.acquire.aligned;" ::: "memory");
}
__device__ __forceinline__ uint32_t cluster_ctarank() {
  uint32_t r;
  asm volatile("mov.u32 %0, %%cluster_ctarank;" : "=r"(r));
  return r;
}

__device__ __forceinline__ uint64_t desc_sw128(uint32_t addr, uint32_t lbo_bytes, uint32_t sbo_bytes) {
  uint64_t d = 0;
  d |= (uint64_t)((addr & 0x3FFFF) >> 4);
  d |= (uint64_t)((lbo_bytes & 0x3FFFF) >> 4) << 16;
  d |= (uint64_t)((sbo_bytes & 0x3FFFF) >> 4) << 32;
  d |= (uint64_t)1 << 62;
  return d;
}

template <int TNSPB, int SCALEA>
__device__ __forceinline__ void wgmma_n128(float (&d)[64], uint64_t da, uint64_t db, int scaleD) {
  asm volatile("{\n.reg .pred p;\nsetp.ne.b32 p, %66, 0;\n"
    "wgmma.mma_async.sync.aligned.m64n128k16.f32.bf16.bf16 {%0, %1, %2, %3, %4, %5, %6, %7, %8, %9, %10, %11, %12, %13, %14, %15, %16, %17, %18, %19, %20, %21, %22, %23, %24, %25, %26, %27, %28, %29, %30, %31, %32, %33, %34, %35, %36, %37, %38, %39, %40, %41, %42, %43, %44, %45, %46, %47, %48, %49, %50, %51, %52, %53, %54, %55, %56, %57, %58, %59, %60, %61, %62, %63}, %64, %65, p, %68, 1, 0, %67;\n}\n"
    : "+f"(d[0]), "+f"(d[1]), "+f"(d[2]), "+f"(d[3]), "+f"(d[4]), "+f"(d[5]), "+f"(d[6]), "+f"(d[7]), "+f"(d[8]), "+f"(d[9]), "+f"(d[10]), "+f"(d[11]), "+f"(d[12]), "+f"(d[13]), "+f"(d[14]), "+f"(d[15]), "+f"(d[16]), "+f"(d[17]), "+f"(d[18]), "+f"(d[19]), "+f"(d[20]), "+f"(d[21]), "+f"(d[22]), "+f"(d[23]), "+f"(d[24]), "+f"(d[25]), "+f"(d[26]), "+f"(d[27]), "+f"(d[28]), "+f"(d[29]), "+f"(d[30]), "+f"(d[31]), "+f"(d[32]), "+f"(d[33]), "+f"(d[34]), "+f"(d[35]), "+f"(d[36]), "+f"(d[37]), "+f"(d[38]), "+f"(d[39]), "+f"(d[40]), "+f"(d[41]), "+f"(d[42]), "+f"(d[43]), "+f"(d[44]), "+f"(d[45]), "+f"(d[46]), "+f"(d[47]), "+f"(d[48]), "+f"(d[49]), "+f"(d[50]), "+f"(d[51]), "+f"(d[52]), "+f"(d[53]), "+f"(d[54]), "+f"(d[55]), "+f"(d[56]), "+f"(d[57]), "+f"(d[58]), "+f"(d[59]), "+f"(d[60]), "+f"(d[61]), "+f"(d[62]), "+f"(d[63])
    : "l"(da), "l"(db), "r"(scaleD), "n"(TNSPB), "n"(SCALEA));
}

template <int TNSPB, int SCALEA>
__device__ __forceinline__ void wgmma_n176(float (&d)[88], uint64_t da, uint64_t db, int scaleD) {
  asm volatile("{\n.reg .pred p;\nsetp.ne.b32 p, %90, 0;\n"
    "wgmma.mma_async.sync.aligned.m64n176k16.f32.bf16.bf16 {%0, %1, %2, %3, %4, %5, %6, %7, %8, %9, %10, %11, %12, %13, %14, %15, %16, %17, %18, %19, %20, %21, %22, %23, %24, %25, %26, %27, %28, %29, %30, %31, %32, %33, %34, %35, %36, %37, %38, %39, %40, %41, %42, %43, %44, %45, %46, %47, %48, %49, %50, %51, %52, %53, %54, %55, %56, %57, %58, %59, %60, %61, %62, %63, %64, %65, %66, %67, %68, %69, %70, %71, %72, %73, %74, %75, %76, %77, %78, %79, %80, %81, %82, %83, %84, %85, %86, %87}, %88, %89, p, %92, 1, 0, %91;\n}\n"
    : "+f"(d[0]), "+f"(d[1]), "+f"(d[2]), "+f"(d[3]), "+f"(d[4]), "+f"(d[5]), "+f"(d[6]), "+f"(d[7]), "+f"(d[8]), "+f"(d[9]), "+f"(d[10]), "+f"(d[11]), "+f"(d[12]), "+f"(d[13]), "+f"(d[14]), "+f"(d[15]), "+f"(d[16]), "+f"(d[17]), "+f"(d[18]), "+f"(d[19]), "+f"(d[20]), "+f"(d[21]), "+f"(d[22]), "+f"(d[23]), "+f"(d[24]), "+f"(d[25]), "+f"(d[26]), "+f"(d[27]), "+f"(d[28]), "+f"(d[29]), "+f"(d[30]), "+f"(d[31]), "+f"(d[32]), "+f"(d[33]), "+f"(d[34]), "+f"(d[35]), "+f"(d[36]), "+f"(d[37]), "+f"(d[38]), "+f"(d[39]), "+f"(d[40]), "+f"(d[41]), "+f"(d[42]), "+f"(d[43]), "+f"(d[44]), "+f"(d[45]), "+f"(d[46]), "+f"(d[47]), "+f"(d[48]), "+f"(d[49]), "+f"(d[50]), "+f"(d[51]), "+f"(d[52]), "+f"(d[53]), "+f"(d[54]), "+f"(d[55]), "+f"(d[56]), "+f"(d[57]), "+f"(d[58]), "+f"(d[59]), "+f"(d[60]), "+f"(d[61]), "+f"(d[62]), "+f"(d[63]), "+f"(d[64]), "+f"(d[65]), "+f"(d[66]), "+f"(d[67]), "+f"(d[68]), "+f"(d[69]), "+f"(d[70]), "+f"(d[71]), "+f"(d[72]), "+f"(d[73]), "+f"(d[74]), "+f"(d[75]), "+f"(d[76]), "+f"(d[77]), "+f"(d[78]), "+f"(d[79]), "+f"(d[80]), "+f"(d[81]), "+f"(d[82]), "+f"(d[83]), "+f"(d[84]), "+f"(d[85]), "+f"(d[86]), "+f"(d[87])
    : "l"(da), "l"(db), "r"(scaleD), "n"(TNSPB), "n"(SCALEA));
}

__device__ __forceinline__ float bf16_round(float v) { return __bfloat162float(__float2bfloat16(v)); }
__device__ __forceinline__ uint32_t pack_bf16(float lo, float hi) {
  __nv_bfloat162 t = __floats2bfloat162_rn(lo, hi);
  return *reinterpret_cast<uint32_t*>(&t);
}
__device__ __forceinline__ float2 unpack_bf16(uint32_t u) {
  __nv_bfloat162 t = *reinterpret_cast<__nv_bfloat162*>(&u);
  return __bfloat1622float2(t);
}
__device__ __forceinline__ float warp_sum(float v) {
#pragma unroll
  for (int o = 16; o > 0; o >>= 1) v += __shfl_xor_sync(0xffffffffu, v, o);
  return v;
}

__global__ void __launch_bounds__(256) k_mod(const __nv_bfloat16* __restrict__ c, const __nv_bfloat16* __restrict__ w_mod) {
  __shared__ float red[32][65];
  __shared__ float sc[D_];
  TL(0, 0, threadIdx.x == 0);
  griddep_launch();
  for (int i = threadIdx.x; i < D_; i += 256) {
    float v = __bfloat162float(c[i]);
    sc[i] = bf16_round(v / (1.0f + __expf(-v)));
  }
  __syncthreads();
  const int tx = threadIdx.x & 7, ty = threadIdx.x >> 3;
  const int col = blockIdx.x * 64 + tx * 8;
  float acc[8];
#pragma unroll
  for (int j = 0; j < 8; j++) acc[j] = 0.f;
  uint4 v[16];
#pragma unroll
  for (int r = 0; r < 16; r++) v[r] = __ldg(reinterpret_cast<const uint4*>(w_mod + (size_t)(ty * 16 + r) * (6 * D_) + col));
#pragma unroll
  for (int r = 0; r < 16; r++) {
    float s = sc[ty * 16 + r];
    const uint32_t* u = reinterpret_cast<const uint32_t*>(&v[r]);
#pragma unroll
    for (int j = 0; j < 4; j++) {
      float2 f = unpack_bf16(u[j]);
      acc[2 * j] += s * f.x;
      acc[2 * j + 1] += s * f.y;
    }
  }
#pragma unroll
  for (int j = 0; j < 8; j++) red[ty][tx * 8 + j] = acc[j];
  __syncthreads();
  if (threadIdx.x < 64) {
    float s = 0.f;
#pragma unroll
    for (int r = 0; r < 32; r++) s += red[r][threadIdx.x];
    g_mod[blockIdx.x * 64 + threadIdx.x] = bf16_round(s);
  }
  TL(0, 1, threadIdx.x == 0);
}

template <int MODE>
struct LnCfg;
template <>
struct LnCfg<0> { static constexpr int BN = 128, STAGE_BYTES = 16384, STAGES = 4, LDO = 1024, NTOT = 1024; };
template <>
struct LnCfg<1> { static constexpr int BN = 176, STAGE_BYTES = 24576, STAGES = 3, LDO = DFF_, NTOT = DFF_; };

constexpr int LN_A_BYTES = 128 * 512 * 2;

template <int MODE>
__global__ void __launch_bounds__(384, 1)
k_ln_gemm(const __grid_constant__ CUtensorMap mapB0, const __grid_constant__ CUtensorMap mapB1,
          const __nv_bfloat16* __restrict__ xin, __nv_bfloat16* __restrict__ out) {
  using C = LnCfg<MODE>;
  constexpr int BN = C::BN, STAGES = C::STAGES, KT = 8;
  extern __shared__ __align__(1024) uint8_t smem[];
  uint8_t* sA = smem;
  uint8_t* sB = smem + LN_A_BYTES;
  uint64_t* bars = reinterpret_cast<uint64_t*>(smem + LN_A_BYTES + STAGES * C::STAGE_BYTES);
  const uint32_t full0 = smem_u32(bars), empty0 = smem_u32(bars + STAGES);

  const int tid = threadIdx.x, warp = tid >> 5, lane = tid & 31;
  const int m0 = blockIdx.y * 128, n0 = blockIdx.x * BN;
  TL(4 + MODE * 8, 0, tid == 0);
  const CUtensorMap* mapB = &mapB0;
  int nb = n0;
  if (MODE == 0 && n0 >= 512) { mapB = &mapB1; nb = n0 - 512; }

  if (tid == 0) {
    for (int s = 0; s < STAGES; s++) { mbar_init(full0 + 8 * s, 1); mbar_init(empty0 + 8 * s, 8); }
    asm volatile("fence.mbarrier_init.release.cluster;" ::: "memory");
    fence_proxy_async();
  }
  __syncthreads();

  auto issue_b = [&](int kt, int s) {
    const uint32_t bar = full0 + 8 * s;
    const uint32_t dst = smem_u32(sB + s * C::STAGE_BYTES);
    mbar_expect_tx(bar, C::STAGE_BYTES);
    if (MODE == 0) {
      tma_load_2d(dst, mapB, kt * 64, nb, bar);
    } else {
#pragma unroll
      for (int j = 0; j < 3; j++) tma_load_2d(dst + j * 8192, mapB, nb + j * 64, kt * 64, bar);
    }
  };
  if (tid == 0) {
    for (int s = 0; s < STAGES; s++) issue_b(s, s);
  }

  griddep_wait();
  TL(4 + MODE * 8, 1, tid == 0);
  griddep_launch();

  {
    const float* scl = g_mod + (MODE == 0 ? 1 : 4) * D_;
    const float* sft = g_mod + (MODE == 0 ? 0 : 3) * D_;
    float sc[16], sh[16];
#pragma unroll
    for (int h = 0; h < 2; h++)
#pragma unroll
      for (int j = 0; j < 8; j++) {
        const int col = h * 256 + lane * 8 + j;
        sc[h * 8 + j] = bf16_round(1.0f + scl[col]);
        sh[h * 8 + j] = sft[col];
      }
    for (int base = warp * 4; base < 128; base += 48) {
      uint4 v0[4], v1[4];
#pragma unroll
      for (int i = 0; i < 4; i++) {
        const uint4* src = reinterpret_cast<const uint4*>(xin + (size_t)(m0 + base + i) * D_);
        v0[i] = src[lane];
        v1[i] = src[lane + 32];
      }
#pragma unroll
      for (int i = 0; i < 4; i++) {
        const int row = base + i;
        float f[16];
        {
          const uint32_t* u0 = reinterpret_cast<const uint32_t*>(&v0[i]);
          const uint32_t* u1 = reinterpret_cast<const uint32_t*>(&v1[i]);
#pragma unroll
          for (int j = 0; j < 4; j++) {
            float2 a = unpack_bf16(u0[j]), b = unpack_bf16(u1[j]);
            f[2 * j] = a.x; f[2 * j + 1] = a.y; f[8 + 2 * j] = b.x; f[8 + 2 * j + 1] = b.y;
          }
        }
        float s = 0.f;
#pragma unroll
        for (int j = 0; j < 16; j++) s += f[j];
        const float mean = warp_sum(s) * (1.0f / D_);
        float q = 0.f;
#pragma unroll
        for (int j = 0; j < 16; j++) { float d = f[j] - mean; q += d * d; }
        const float rstd = rsqrtf(warp_sum(q) * (1.0f / D_) + 1e-5f);
        uint4 o0, o1;
        uint32_t* p0 = reinterpret_cast<uint32_t*>(&o0);
        uint32_t* p1 = reinterpret_cast<uint32_t*>(&o1);
#pragma unroll
        for (int j = 0; j < 4; j++) {
          p0[j] = pack_bf16((f[2 * j] - mean) * rstd * sc[2 * j] + sh[2 * j], (f[2 * j + 1] - mean) * rstd * sc[2 * j + 1] + sh[2 * j + 1]);
          p1[j] = pack_bf16((f[8 + 2 * j] - mean) * rstd * sc[8 + 2 * j] + sh[8 + 2 * j],
                            (f[8 + 2 * j + 1] - mean) * rstd * sc[8 + 2 * j + 1] + sh[8 + 2 * j + 1]);
        }
        const int c0 = lane, c1 = lane + 32;
        *reinterpret_cast<uint4*>(sA + (c0 >> 3) * 16384 + row * 128 + (((c0 & 7) ^ (row & 7)) << 4)) = o0;
        *reinterpret_cast<uint4*>(sA + (c1 >> 3) * 16384 + row * 128 + (((c1 & 7) ^ (row & 7)) << 4)) = o1;
      }
    }
  }
  fence_proxy_async();
  __syncthreads();
  TL(5 + MODE * 8, 0, tid == 0);

  if (warp < 4) {
    if (tid == 0) {
      for (int kt = STAGES; kt < KT; kt++) {
        const int s = kt % STAGES;
        mbar_wait(empty0 + 8 * s, ((kt / STAGES) - 1) & 1);
        issue_b(kt, s);
      }
    }
  } else {
    const int wg = (warp >> 2) - 1;
    float acc[BN / 2];
#pragma unroll
    for (int i = 0; i < BN / 2; i++) acc[i] = 0.f;
    const uint32_t a_base = smem_u32(sA) + wg * 8192;
    for (int kt = 0; kt < KT; kt++) {
      const int s = kt % STAGES;
      mbar_wait(full0 + 8 * s, (kt / STAGES) & 1);
      wgmma_fence();
      const uint32_t bs = smem_u32(sB + s * C::STAGE_BYTES);
#pragma unroll
      for (int k = 0; k < 4; k++) {
        const uint64_t da = desc_sw128(a_base + kt * 16384 + k * 32, 16, 1024);
        if (MODE == 0) {
          const uint64_t db = desc_sw128(bs + k * 32, 16, 1024);
          wgmma_n128<0, 1>(*reinterpret_cast<float(*)[64]>(acc), da, db, 1);
        } else {
          const uint64_t db = desc_sw128(bs + k * 2048, 8192, 1024);
          wgmma_n176<1, 1>(*reinterpret_cast<float(*)[88]>(acc), da, db, 1);
        }
      }
      wgmma_commit();
      wgmma_wait<1>();
      if (kt > 0 && lane == 0) mbar_arrive(empty0 + 8 * ((kt - 1) % STAGES));
    }
    wgmma_wait<0>();
    named_bar_sync(1, 256);
    TL(5 + MODE * 8, 1, tid == 128);
    constexpr int LDS = BN * 2 + 16;
    uint8_t* st = sA + (warp - 4) * (16 * LDS);
    {
      const int r = lane >> 2, cq = (lane & 3) * 2;
#pragma unroll
      for (int j = 0; j < BN / 8; j++) {
        float v0 = acc[4 * j], v1 = acc[4 * j + 1], v2 = acc[4 * j + 2], v3 = acc[4 * j + 3];
        if (MODE == 1) { v0 = fmaxf(v0, 0.f); v1 = fmaxf(v1, 0.f); v2 = fmaxf(v2, 0.f); v3 = fmaxf(v3, 0.f); }
        *reinterpret_cast<uint32_t*>(st + r * LDS + (j * 8 + cq) * 2) = pack_bf16(v0, v1);
        *reinterpret_cast<uint32_t*>(st + (r + 8) * LDS + (j * 8 + cq) * 2) = pack_bf16(v2, v3);
      }
    }
    __syncwarp();
    constexpr int CH = BN / 8;
    const int mrow = m0 + wg * 64 + (warp & 3) * 16;
    for (int idx = lane; idx < 16 * CH; idx += 32) {
      const int r = idx / CH, ch = idx % CH;
      if (n0 + ch * 8 < C::NTOT) {
        uint4 v = *reinterpret_cast<const uint4*>(st + r * LDS + ch * 16);
        *reinterpret_cast<uint4*>(out + (size_t)(mrow + r) * C::LDO + n0 + ch * 8) = v;
      }
    }
    TL(6 + MODE * 8, 0, tid == 128); TL(6 + MODE * 8, 1, tid == 128);
  }
}

constexpr int SK_STAGES = 4;
constexpr int SK_STAGE_BYTES = 32768;
constexpr int SK_XCH_BYTES = 32768;

template <int MODE>
__global__ void __cluster_dims__(2, 1, 1) __launch_bounds__(384, 1)
k_sk_gemm(const __grid_constant__ CUtensorMap mapA0, const __grid_constant__ CUtensorMap mapA1,
          const __grid_constant__ CUtensorMap mapB, const __nv_bfloat16* __restrict__ res,
          __nv_bfloat16* __restrict__ out) {
  constexpr int KT = (MODE == 0) ? 32 : 11;
  extern __shared__ __align__(1024) uint8_t smem[];
  uint8_t* sStage = smem;
  uint8_t* sX = smem + SK_STAGES * SK_STAGE_BYTES;
  uint64_t* bars = reinterpret_cast<uint64_t*>(smem + SK_STAGES * SK_STAGE_BYTES + SK_XCH_BYTES);
  const uint32_t full0 = smem_u32(bars), empty0 = smem_u32(bars + SK_STAGES);

  const int tid = threadIdx.x, warp = tid >> 5, lane = tid & 31;
  const int half = blockIdx.x & 1;
  const int m0 = blockIdx.y * 128, n0 = (blockIdx.x >> 1) * 128;
  TL(8 + MODE * 8, 0, tid == 0);

  if (tid == 0) {
    for (int s = 0; s < SK_STAGES; s++) { mbar_init(full0 + 8 * s, 1); mbar_init(empty0 + 8 * s, 8); }
    asm volatile("fence.mbarrier_init.release.cluster;" ::: "memory");
    fence_proxy_async();
  }
  __syncthreads();
  griddep_wait();
  TL(8 + MODE * 8, 1, tid == 0);
  griddep_launch();

  if (warp < 4) {
    if (tid == 0) {
      const CUtensorMap* mapA = (MODE == 0 && half) ? &mapA1 : &mapA0;
      const int kbase = (MODE == 0) ? 0 : half * 11 * 64;
      const int nb = (MODE == 0) ? n0 + half * 512 : n0;
      for (int kt = 0; kt < KT; kt++) {
        const int s = kt % SK_STAGES;
        if (kt >= SK_STAGES) mbar_wait(empty0 + 8 * s, ((kt / SK_STAGES) - 1) & 1);
        const uint32_t bar = full0 + 8 * s;
        const uint32_t dst = smem_u32(sStage + s * SK_STAGE_BYTES);
        mbar_expect_tx(bar, SK_STAGE_BYTES);
        tma_load_2d(dst, mapA, kbase + kt * 64, m0, bar);
        tma_load_2d(dst + 16384, &mapB, nb, kbase + kt * 64, bar);
        tma_load_2d(dst + 16384 + 8192, &mapB, nb + 64, kbase + kt * 64, bar);
      }
    }
    cluster_sync_all();
  } else {
    const int wg = (warp >> 2) - 1;
    float acc[64];
#pragma unroll
    for (int i = 0; i < 64; i++) acc[i] = 0.f;
    for (int kt = 0; kt < KT; kt++) {
      const int s = kt % SK_STAGES;
      mbar_wait(full0 + 8 * s, (kt / SK_STAGES) & 1);
      wgmma_fence();
      const uint32_t as = smem_u32(sStage + s * SK_STAGE_BYTES) + wg * 8192;
      const uint32_t bs = smem_u32(sStage + s * SK_STAGE_BYTES) + 16384;
#pragma unroll
      for (int k = 0; k < 4; k++) {
        const uint64_t da = desc_sw128(as + k * 32, 16, 1024);
        const uint64_t db = desc_sw128(bs + k * 2048, 8192, 1024);
        wgmma_n128<1, 1>(acc, da, db, 1);
      }
      wgmma_commit();
      wgmma_wait<1>();
      if (kt > 0 && lane == 0) mbar_arrive(empty0 + 8 * ((kt - 1) % SK_STAGES));
    }
    wgmma_wait<0>();
    TL(9 + MODE * 8, 0, tid == 128);
    const int t = tid & 127;
    {
      uint32_t remote;
      asm volatile("mapa.shared::cluster.u32 %0, %1, %2;" : "=r"(remote) : "r"(smem_u32(sX)), "r"(half ^ 1));
#pragma unroll
      for (int i = 0; i < 8; i++) {
        const int b = (half ^ 1) * 32 + 4 * i;
        asm volatile("st.shared::cluster.v4.f32 [%0], {%1, %2, %3, %4};" ::"r"(remote + ((wg * 8 + i) * 128 + t) * 16),
                     "f"(half ? acc[4 * i] : acc[32 + 4 * i]), "f"(half ? acc[4 * i + 1] : acc[32 + 4 * i + 1]),
                     "f"(half ? acc[4 * i + 2] : acc[32 + 4 * i + 2]), "f"(half ? acc[4 * i + 3] : acc[32 + 4 * i + 3])
                     : "memory");
        (void)b;
      }
    }
    cluster_sync_all();
    TL(9 + MODE * 8, 1, tid == 128);
    {
      constexpr int LDSF = 68;
      float* st = reinterpret_cast<float*>(sStage) + (warp - 4) * (16 * LDSF);
      const int r = lane >> 2, cq = (lane & 3) * 2;
#pragma unroll
      for (int j = 0; j < 8; j++) {
        const float4 o = *reinterpret_cast<const float4*>(sX + ((wg * 8 + j) * 128 + t) * 16);
        float a0 = half ? acc[32 + 4 * j] : acc[4 * j], a1 = half ? acc[32 + 4 * j + 1] : acc[4 * j + 1];
        float a2 = half ? acc[32 + 4 * j + 2] : acc[4 * j + 2], a3 = half ? acc[32 + 4 * j + 3] : acc[4 * j + 3];
        float v0, v1, v2, v3;
        if (MODE == 0) {
          if (half == 0) { v0 = a0 - o.x; v1 = a1 - o.y; v2 = a2 - o.z; v3 = a3 - o.w; }
          else { v0 = o.x - a0; v1 = o.y - a1; v2 = o.z - a2; v3 = o.w - a3; }
        } else {
          v0 = a0 + o.x; v1 = a1 + o.y; v2 = a2 + o.z; v3 = a3 + o.w;
        }
        *reinterpret_cast<float2*>(st + r * LDSF + j * 8 + cq) = make_float2(v0, v1);
        *reinterpret_cast<float2*>(st + (r + 8) * LDSF + j * 8 + cq) = make_float2(v2, v3);
      }
      __syncwarp();
      const float* gate = g_mod + (MODE == 0 ? 2 : 5) * D_;
      const int cbase = n0 + half * 64 + (lane & 7) * 8;
      float g[8];
#pragma unroll
      for (int j = 0; j < 8; j++) g[j] = gate[cbase + j];
      const int rbase = m0 + wg * 64 + (warp & 3) * 16;
      uint4 rv[4];
#pragma unroll
      for (int i = 0; i < 4; i++) rv[i] = *reinterpret_cast<const uint4*>(res + (size_t)(rbase + i * 4 + (lane >> 3)) * D_ + cbase);
#pragma unroll
      for (int i = 0; i < 4; i++) {
        const int rr = i * 4 + (lane >> 3);
        const float4 f0 = *reinterpret_cast<const float4*>(st + rr * LDSF + (lane & 7) * 8);
        const float4 f1 = *reinterpret_cast<const float4*>(st + rr * LDSF + (lane & 7) * 8 + 4);
        const uint32_t* ru = reinterpret_cast<const uint32_t*>(&rv[i]);
        uint4 o;
        uint32_t* ou = reinterpret_cast<uint32_t*>(&o);
        float2 q;
        q = unpack_bf16(ru[0]); ou[0] = pack_bf16(q.x + g[0] * f0.x, q.y + g[1] * f0.y);
        q = unpack_bf16(ru[1]); ou[1] = pack_bf16(q.x + g[2] * f0.z, q.y + g[3] * f0.w);
        q = unpack_bf16(ru[2]); ou[2] = pack_bf16(q.x + g[4] * f1.x, q.y + g[5] * f1.y);
        q = unpack_bf16(ru[3]); ou[3] = pack_bf16(q.x + g[6] * f1.z, q.y + g[7] * f1.w);
        *reinterpret_cast<uint4*>(out + (size_t)(rbase + rr) * D_ + cbase) = o;
      }
      TL(10 + MODE * 8, 0, tid == 128); TL(10 + MODE * 8, 1, tid == 128);
    }
  }
}

typedef CUresult (*PFN_encodeTiled_t)(CUtensorMap*, CUtensorMapDataType, cuuint32_t, void*, const cuuint64_t*,
                                      const cuuint64_t*, const cuuint32_t*, const cuuint32_t*, CUtensorMapInterleave,
                                      CUtensorMapSwizzle, CUtensorMapL2promotion, CUtensorMapFloatOOBfill);

CUtensorMap make_map(PFN_encodeTiled_t enc, const void* ptr, uint64_t inner, uint64_t outer, uint32_t box_inner,
                     uint32_t box_outer) {
  CUtensorMap m;
  cuuint64_t dims[2] = {inner, outer};
  cuuint64_t strides[1] = {inner * 2};
  cuuint32_t box[2] = {box_inner, box_outer};
  cuuint32_t es[2] = {1, 1};
  enc(&m, CU_TENSOR_MAP_DATA_TYPE_BFLOAT16, 2, const_cast<void*>(ptr), dims, strides, box, es,
      CU_TENSOR_MAP_INTERLEAVE_NONE, CU_TENSOR_MAP_SWIZZLE_128B, CU_TENSOR_MAP_L2_PROMOTION_L2_256B,
      CU_TENSOR_MAP_FLOAT_OOB_FILL_NONE);
  return m;
}

template <typename... KArgs, typename... Args>
void launch(void (*kern)(KArgs...), dim3 grid, dim3 block, size_t smem, bool pdl, Args... args) {
  cudaLaunchConfig_t cfg = {};
  cfg.gridDim = grid;
  cfg.blockDim = block;
  cfg.dynamicSmemBytes = smem;
  cfg.stream = cudaStreamPerThread;
  cudaLaunchAttribute at[1];
  at[0].id = cudaLaunchAttributeProgrammaticStreamSerialization;
  at[0].val.programmaticStreamSerializationAllowed = 1;
  cfg.attrs = at;
  cfg.numAttrs = pdl ? 1 : 0;
  cudaLaunchKernelEx(&cfg, kern, KArgs(args)...);
}

}

extern "C" void kernel_launch(void* const* d_in, const int* in_sizes, int n_in, void* d_out, int out_size) {
  const __nv_bfloat16* x = (const __nv_bfloat16*)d_in[0];
  const __nv_bfloat16* ws_re = (const __nv_bfloat16*)d_in[1];
  const __nv_bfloat16* ws_im = (const __nv_bfloat16*)d_in[2];
  const __nv_bfloat16* wd_re = (const __nv_bfloat16*)d_in[3];
  const __nv_bfloat16* wd_im = (const __nv_bfloat16*)d_in[4];
  const __nv_bfloat16* w1 = (const __nv_bfloat16*)d_in[6];
  const __nv_bfloat16* w2 = (const __nv_bfloat16*)d_in[7];
  const __nv_bfloat16* c = (const __nv_bfloat16*)d_in[8];
  const __nv_bfloat16* w_mod = (const __nv_bfloat16*)d_in[9];
  __nv_bfloat16* out = (__nv_bfloat16*)d_out;

  void* fn = nullptr;
  cudaDriverEntryPointQueryResult qres;
  cudaGetDriverEntryPoint("cuTensorMapEncodeTiled", &fn, cudaEnableDefault, &qres);
  PFN_encodeTiled_t enc = (PFN_encodeTiled_t)fn;

  void *p_ab, *p_x1, *p_h1;
  cudaGetSymbolAddress(&p_ab, g_ab);
  cudaGetSymbolAddress(&p_x1, g_x1);
  cudaGetSymbolAddress(&p_h1, g_h1);

  const CUtensorMap m_wd_re = make_map(enc, wd_re, D_, D_, 64, 128);
  const CUtensorMap m_wd_im = make_map(enc, wd_im, D_, D_, 64, 128);
  const CUtensorMap m_ws_re = make_map(enc, ws_re, S_, S_, 64, 128);
  const CUtensorMap m_ws_im = make_map(enc, ws_im, S_, S_, 64, 128);
  const CUtensorMap m_ab = make_map(enc, p_ab, 2 * D_, S_, 64, 64);
  const CUtensorMap m_w1 = make_map(enc, w1, DFF_, D_, 64, 64);
  const CUtensorMap m_h1 = make_map(enc, p_h1, DFF_, S_, 64, 128);
  const CUtensorMap m_w2 = make_map(enc, w2, D_, DFF_, 64, 64);

  constexpr int SM_K1 = LN_A_BYTES + LnCfg<0>::STAGES * LnCfg<0>::STAGE_BYTES + 256;
  constexpr int SM_K3 = LN_A_BYTES + LnCfg<1>::STAGES * LnCfg<1>::STAGE_BYTES + 256;
  constexpr int SM_SK = SK_STAGES * SK_STAGE_BYTES + SK_XCH_BYTES + 256;
  cudaFuncSetAttribute(k_ln_gemm<0>, cudaFuncAttributeMaxDynamicSharedMemorySize, SM_K1);
  cudaFuncSetAttribute(k_ln_gemm<1>, cudaFuncAttributeMaxDynamicSharedMemorySize, SM_K3);
  cudaFuncSetAttribute(k_sk_gemm<0>, cudaFuncAttributeMaxDynamicSharedMemorySize, SM_SK);
  cudaFuncSetAttribute(k_sk_gemm<1>, cudaFuncAttributeMaxDynamicSharedMemorySize, SM_SK);

  launch(k_mod, dim3(48), dim3(256), 0, false, c, w_mod);
  launch(k_ln_gemm<0>, dim3(8, 16), dim3(384), SM_K1, true, m_wd_re, m_wd_im, x, (__nv_bfloat16*)p_ab);
  launch(k_sk_gemm<0>, dim3(8, 16), dim3(384), SM_SK, true, m_ws_re, m_ws_im, m_ab, x, (__nv_bfloat16*)p_x1);
  launch(k_ln_gemm<1>, dim3(8, 16), dim3(384), SM_K3, true, m_w1, m_w1, (const __nv_bfloat16*)p_x1, (__nv_bfloat16*)p_h1);
  launch(k_sk_gemm<1>, dim3(8, 16), dim3(384), SM_SK, true, m_h1, m_h1, m_w2, (const __nv_bfloat16*)p_x1, out);
}
```

```cpp
#include <cuda_runtime.h>
#include <cuda_bf16.h>
#include <cuda.h>
#include <stdint.h>

namespace {

constexpr int S_ = 2048, D_ = 512, DFF_ = 1376;

__device__ __align__(1024) float          g_mod[6 * D_];
__device__ __align__(1024) __nv_bfloat16  g_ab[S_ * 2 * D_];
__device__ __align__(1024) __nv_bfloat16  g_x1[S_ * D_];
__device__ __align__(1024) __nv_bfloat16  g_h2[S_ * D_];
__device__ __align__(1024) __nv_bfloat16  g_h1[S_ * DFF_];

#define TL(slot, which, cond)

__device__ __forceinline__ uint32_t smem_u32(const void* p) { return (uint32_t)__cvta_generic_to_shared(p); }

__device__ __forceinline__ void mbar_init(uint32_t bar, uint32_t count) {
  asm volatile("mbarrier.init.shared::cta.b64 [%0], %1;" ::"r"(bar), "r"(count) : "memory");
}
__device__ __forceinline__ void mbar_expect_tx(uint32_t bar, uint32_t bytes) {
  asm volatile("mbarrier.arrive.expect_tx.shared::cta.b64 _, [%0], %1;" ::"r"(bar), "r"(bytes) : "memory");
}
__device__ __forceinline__ void mbar_arrive(uint32_t bar) {
  asm volatile("mbarrier.arrive.shared::cta.b64 _, [%0];" ::"r"(bar) : "memory");
}
__device__ __forceinline__ uint32_t mapa(uint32_t addr, uint32_t rank) {
  uint32_t r;
  asm volatile("mapa.shared::cluster.u32 %0, %1, %2;" : "=r"(r) : "r"(addr), "r"(rank));
  return r;
}
__device__ __forceinline__ void mbar_arrive_remote(uint32_t bar, uint32_t rank) {
  asm volatile("mbarrier.arrive.release.cluster.shared::cluster.b64 _, [%0];" ::"r"(mapa(bar, rank)) : "memory");
}
__device__ __forceinline__ bool mbar_try_wait(uint32_t bar, uint32_t parity) {
  uint32_t ok;
  asm volatile(
      "{\n.reg .pred p;\n"
      "mbarrier.try_wait.parity.shared::cta.b64 p, [%1], %2;\n"
      "selp.u32 %0, 1, 0, p;\n}\n"
      : "=r"(ok)
      : "r"(bar), "r"(parity)
      : "memory");
  return ok != 0;
}
__device__ __forceinline__ void mbar_wait(uint32_t bar, uint32_t parity) {
  uint32_t spins = 0;
  while (!mbar_try_wait(bar, parity)) {
    if (++spins > (1u << 24)) __trap();
  }
}
__device__ __forceinline__ void tma_load_2d(uint32_t dst, const CUtensorMap* map, int c0, int c1, uint32_t bar) {
  asm volatile(
      "cp.async.bulk.tensor.2d.shared::cluster.global.mbarrier::complete_tx::bytes [%0], [%1, {%3, %4}], [%2];"
      ::"r"(dst), "l"(map), "r"(bar), "r"(c0), "r"(c1)
      : "memory");
}
__device__ __forceinline__ void tma_load_2d_mc(uint32_t dst, const CUtensorMap* map, int c0, int c1, uint32_t bar,
                                               uint16_t mask) {
  asm volatile(
      "cp.async.bulk.tensor.2d.shared::cluster.global.mbarrier::complete_tx::bytes.multicast::cluster [%0], [%1, {%3, %4}], [%2], %5;"
      ::"r"(dst), "l"(map), "r"(bar), "r"(c0), "r"(c1), "h"(mask)
      : "memory");
}
__device__ __forceinline__ void wgmma_fence() { asm volatile("wgmma.fence.sync.aligned;" ::: "memory"); }
__device__ __forceinline__ void wgmma_commit() { asm volatile("wgmma.commit_group.sync.aligned;" ::: "memory"); }
template <int N>
__device__ __forceinline__ void wgmma_wait() { asm volatile("wgmma.wait_group.sync.aligned %0;" ::"n"(N) : "memory"); }
__device__ __forceinline__ void fence_proxy_async() { asm volatile("fence.proxy.async.shared::cta;" ::: "memory"); }
__device__ __forceinline__ void named_bar_sync(int id, int nthreads) {
  asm volatile("bar.sync %0, %1;" ::"r"(id), "r"(nthreads) : "memory");
}
__device__ __forceinline__ void griddep_wait() { asm volatile("griddepcontrol.wait;" ::: "memory"); }
__device__ __forceinline__ void griddep_launch() { asm volatile("griddepcontrol.launch_dependents;" ::: "memory"); }
__device__ __forceinline__ void cluster_sync_all() {
  asm volatile("barrier.cluster.arrive.release.aligned;\nbarrier.cluster.wait.acquire.aligned;" ::: "memory");
}

__device__ __forceinline__ uint64_t desc_sw128(uint32_t addr, uint32_t lbo_bytes, uint32_t sbo_bytes) {
  uint64_t d = 0;
  d |= (uint64_t)((addr & 0x3FFFF) >> 4);
  d |= (uint64_t)((lbo_bytes & 0x3FFFF) >> 4) << 16;
  d |= (uint64_t)((sbo_bytes & 0x3FFFF) >> 4) << 32;
  d |= (uint64_t)1 << 62;
  return d;
}

template <int TNSPB, int SCALEA>
__device__ __forceinline__ void wgmma_n128(float (&d)[64], uint64_t da, uint64_t db, int scaleD) {
  asm volatile("{\n.reg .pred p;\nsetp.ne.b32 p, %66, 0;\n"
    "wgmma.mma_async.sync.aligned.m64n128k16.f32.bf16.bf16 {%0, %1, %2, %3, %4, %5, %6, %7, %8, %9, %10, %11, %12, %13, %14, %15, %16, %17, %18, %19, %20, %21, %22, %23, %24, %25, %26, %27, %28, %29, %30, %31, %32, %33, %34, %35, %36, %37, %38, %39, %40, %41, %42, %43, %44, %45, %46, %47, %48, %49, %50, %51, %52, %53, %54, %55, %56, %57, %58, %59, %60, %61, %62, %63}, %64, %65, p, %68, 1, 0, %67;\n}\n"
    : "+f"(d[0]), "+f"(d[1]), "+f"(d[2]), "+f"(d[3]), "+f"(d[4]), "+f"(d[5]), "+f"(d[6]), "+f"(d[7]), "+f"(d[8]), "+f"(d[9]), "+f"(d[10]), "+f"(d[11]), "+f"(d[12]), "+f"(d[13]), "+f"(d[14]), "+f"(d[15]), "+f"(d[16]), "+f"(d[17]), "+f"(d[18]), "+f"(d[19]), "+f"(d[20]), "+f"(d[21]), "+f"(d[22]), "+f"(d[23]), "+f"(d[24]), "+f"(d[25]), "+f"(d[26]), "+f"(d[27]), "+f"(d[28]), "+f"(d[29]), "+f"(d[30]), "+f"(d[31]), "+f"(d[32]), "+f"(d[33]), "+f"(d[34]), "+f"(d[35]), "+f"(d[36]), "+f"(d[37]), "+f"(d[38]), "+f"(d[39]), "+f"(d[40]), "+f"(d[41]), "+f"(d[42]), "+f"(d[43]), "+f"(d[44]), "+f"(d[45]), "+f"(d[46]), "+f"(d[47]), "+f"(d[48]), "+f"(d[49]), "+f"(d[50]), "+f"(d[51]), "+f"(d[52]), "+f"(d[53]), "+f"(d[54]), "+f"(d[55]), "+f"(d[56]), "+f"(d[57]), "+f"(d[58]), "+f"(d[59]), "+f"(d[60]), "+f"(d[61]), "+f"(d[62]), "+f"(d[63])
    : "l"(da), "l"(db), "r"(scaleD), "n"(TNSPB), "n"(SCALEA));
}

template <int TNSPB, int SCALEA>
__device__ __forceinline__ void wgmma_n176(float (&d)[88], uint64_t da, uint64_t db, int scaleD) {
  asm volatile("{\n.reg .pred p;\nsetp.ne.b32 p, %90, 0;\n"
    "wgmma.mma_async.sync.aligned.m64n176k16.f32.bf16.bf16 {%0, %1, %2, %3, %4, %5, %6, %7, %8, %9, %10, %11, %12, %13, %14, %15, %16, %17, %18, %19, %20, %21, %22, %23, %24, %25, %26, %27, %28, %29, %30, %31, %32, %33, %34, %35, %36, %37, %38, %39, %40, %41, %42, %43, %44, %45, %46, %47, %48, %49, %50, %51, %52, %53, %54, %55, %56, %57, %58, %59, %60, %61, %62, %63, %64, %65, %66, %67, %68, %69, %70, %71, %72, %73, %74, %75, %76, %77, %78, %79, %80, %81, %82, %83, %84, %85, %86, %87}, %88, %89, p, %92, 1, 0, %91;\n}\n"
    : "+f"(d[0]), "+f"(d[1]), "+f"(d[2]), "+f"(d[3]), "+f"(d[4]), "+f"(d[5]), "+f"(d[6]), "+f"(d[7]), "+f"(d[8]), "+f"(d[9]), "+f"(d[10]), "+f"(d[11]), "+f"(d[12]), "+f"(d[13]), "+f"(d[14]), "+f"(d[15]), "+f"(d[16]), "+f"(d[17]), "+f"(d[18]), "+f"(d[19]), "+f"(d[20]), "+f"(d[21]), "+f"(d[22]), "+f"(d[23]), "+f"(d[24]), "+f"(d[25]), "+f"(d[26]), "+f"(d[27]), "+f"(d[28]), "+f"(d[29]), "+f"(d[30]), "+f"(d[31]), "+f"(d[32]), "+f"(d[33]), "+f"(d[34]), "+f"(d[35]), "+f"(d[36]), "+f"(d[37]), "+f"(d[38]), "+f"(d[39]), "+f"(d[40]), "+f"(d[41]), "+f"(d[42]), "+f"(d[43]), "+f"(d[44]), "+f"(d[45]), "+f"(d[46]), "+f"(d[47]), "+f"(d[48]), "+f"(d[49]), "+f"(d[50]), "+f"(d[51]), "+f"(d[52]), "+f"(d[53]), "+f"(d[54]), "+f"(d[55]), "+f"(d[56]), "+f"(d[57]), "+f"(d[58]), "+f"(d[59]), "+f"(d[60]), "+f"(d[61]), "+f"(d[62]), "+f"(d[63]), "+f"(d[64]), "+f"(d[65]), "+f"(d[66]), "+f"(d[67]), "+f"(d[68]), "+f"(d[69]), "+f"(d[70]), "+f"(d[71]), "+f"(d[72]), "+f"(d[73]), "+f"(d[74]), "+f"(d[75]), "+f"(d[76]), "+f"(d[77]), "+f"(d[78]), "+f"(d[79]), "+f"(d[80]), "+f"(d[81]), "+f"(d[82]), "+f"(d[83]), "+f"(d[84]), "+f"(d[85]), "+f"(d[86]), "+f"(d[87])
    : "l"(da), "l"(db), "r"(scaleD), "n"(TNSPB), "n"(SCALEA));
}

__device__ __forceinline__ float bf16_round(float v) { return __bfloat162float(__float2bfloat16(v)); }
__device__ __forceinline__ uint32_t pack_bf16(float lo, float hi) {
  __nv_bfloat162 t = __floats2bfloat162_rn(lo, hi);
  return *reinterpret_cast<uint32_t*>(&t);
}
__device__ __forceinline__ float2 unpack_bf16(uint32_t u) {
  __nv_bfloat162 t = *reinterpret_cast<__nv_bfloat162*>(&u);
  return __bfloat1622float2(t);
}

__global__ void __launch_bounds__(256) k_mod(const __nv_bfloat16* __restrict__ c, const __nv_bfloat16* __restrict__ w_mod) {
  __shared__ float red[32][65];
  __shared__ float sc[D_];
  TL(0, 0, threadIdx.x == 0);
  griddep_launch();
  const int tx = threadIdx.x & 7, ty = threadIdx.x >> 3;
  const int col = blockIdx.x * 64 + tx * 8;
  uint4 v[16];
#pragma unroll
  for (int r = 0; r < 16; r++) v[r] = __ldg(reinterpret_cast<const uint4*>(w_mod + (size_t)(ty * 16 + r) * (6 * D_) + col));
  for (int i = threadIdx.x; i < D_; i += 256) {
    float x = __bfloat162float(c[i]);
    sc[i] = bf16_round(x / (1.0f + __expf(-x)));
  }
  __syncthreads();
  float acc[8];
#pragma unroll
  for (int j = 0; j < 8; j++) acc[j] = 0.f;
#pragma unroll
  for (int r = 0; r < 16; r++) {
    float s = sc[ty * 16 + r];
    const uint32_t* u = reinterpret_cast<const uint32_t*>(&v[r]);
#pragma unroll
    for (int j = 0; j < 4; j++) {
      float2 f = unpack_bf16(u[j]);
      acc[2 * j] += s * f.x;
      acc[2 * j + 1] += s * f.y;
    }
  }
#pragma unroll
  for (int j = 0; j < 8; j++) red[ty][tx * 8 + j] = acc[j];
  __syncthreads();
  if (threadIdx.x < 64) {
    float s = 0.f;
#pragma unroll
    for (int r = 0; r < 32; r++) s += red[r][threadIdx.x];
    g_mod[blockIdx.x * 64 + threadIdx.x] = bf16_round(s);
  }
  TL(0, 1, threadIdx.x == 0);
}

constexpr int G1_A_BYTES = 128 * 512 * 2;
constexpr int G1_STAGES = 4;
constexpr int G1_STAGE_BYTES = 16384;

__global__ void __launch_bounds__(384, 1)
k_gemm1(const __grid_constant__ CUtensorMap mapB0, const __grid_constant__ CUtensorMap mapB1,
        const __nv_bfloat16* __restrict__ xin, __nv_bfloat16* __restrict__ out) {
  constexpr int KT = 8;
  extern __shared__ __align__(1024) uint8_t smem[];
  uint8_t* sA = smem;
  uint8_t* sB = smem + G1_A_BYTES;
  uint64_t* bars = reinterpret_cast<uint64_t*>(smem + G1_A_BYTES + G1_STAGES * G1_STAGE_BYTES);
  const uint32_t full0 = smem_u32(bars), empty0 = smem_u32(bars + G1_STAGES);

  const int tid = threadIdx.x, warp = tid >> 5, lane = tid & 31;
  const int m0 = blockIdx.y * 128, n0 = blockIdx.x * 128;
  TL(4, 0, tid == 0);
  const CUtensorMap* mapB = n0 >= 512 ? &mapB1 : &mapB0;
  const int nb = n0 & 511;

  if (tid == 0) {
    for (int s = 0; s < G1_STAGES; s++) { mbar_init(full0 + 8 * s, 1); mbar_init(empty0 + 8 * s, 8); }
    asm volatile("fence.mbarrier_init.release.cluster;" ::: "memory");
    fence_proxy_async();
  }
  __syncthreads();

  auto issue_b = [&](int kt, int s) {
    const uint32_t bar = full0 + 8 * s;
    mbar_expect_tx(bar, G1_STAGE_BYTES);
    tma_load_2d(smem_u32(sB + s * G1_STAGE_BYTES), mapB, kt * 64, nb, bar);
  };
  if (tid == 0) {
    for (int s = 0; s < G1_STAGES; s++) issue_b(s, s);
  }

  for (int base = warp * 4; base < 128; base += 48) {
    uint4 v0[4], v1[4];
#pragma unroll
    for (int i = 0; i < 4; i++) {
      const uint4* src = reinterpret_cast<const uint4*>(xin + (size_t)(m0 + base + i) * D_);
      v0[i] = src[lane];
      v1[i] = src[lane + 32];
    }
    float f[4][16], s[4], q[4];
#pragma unroll
    for (int i = 0; i < 4; i++) {
      const uint32_t* u0 = reinterpret_cast<const uint32_t*>(&v0[i]);
      const uint32_t* u1 = reinterpret_cast<const uint32_t*>(&v1[i]);
      s[i] = 0.f;
#pragma unroll
      for (int j = 0; j < 4; j++) {
        float2 a = unpack_bf16(u0[j]), b = unpack_bf16(u1[j]);
        f[i][2 * j] = a.x; f[i][2 * j + 1] = a.y; f[i][8 + 2 * j] = b.x; f[i][8 + 2 * j + 1] = b.y;
        s[i] += (a.x + a.y) + (b.x + b.y);
      }
    }
#pragma unroll
    for (int o = 16; o > 0; o >>= 1)
#pragma unroll
      for (int i = 0; i < 4; i++) s[i] += __shfl_xor_sync(0xffffffffu, s[i], o);
#pragma unroll
    for (int i = 0; i < 4; i++) {
      const float mean = s[i] * (1.0f / D_);
      q[i] = 0.f;
#pragma unroll
      for (int j = 0; j < 16; j++) { f[i][j] -= mean; q[i] += f[i][j] * f[i][j]; }
    }
#pragma unroll
    for (int o = 16; o > 0; o >>= 1)
#pragma unroll
      for (int i = 0; i < 4; i++) q[i] += __shfl_xor_sync(0xffffffffu, q[i], o);
#pragma unroll
    for (int i = 0; i < 4; i++) {
      const int row = base + i;
      const float rstd = rsqrtf(q[i] * (1.0f / D_) + 1e-5f);
      uint4 o0, o1;
      uint32_t* p0 = reinterpret_cast<uint32_t*>(&o0);
      uint32_t* p1 = reinterpret_cast<uint32_t*>(&o1);
#pragma unroll
      for (int j = 0; j < 4; j++) {
        p0[j] = pack_bf16(f[i][2 * j] * rstd, f[i][2 * j + 1] * rstd);
        p1[j] = pack_bf16(f[i][8 + 2 * j] * rstd, f[i][8 + 2 * j + 1] * rstd);
      }
      const int c0 = lane, c1 = lane + 32;
      *reinterpret_cast<uint4*>(sA + (c0 >> 3) * 16384 + row * 128 + (((c0 & 7) ^ (row & 7)) << 4)) = o0;
      *reinterpret_cast<uint4*>(sA + (c1 >> 3) * 16384 + row * 128 + (((c1 & 7) ^ (row & 7)) << 4)) = o1;
    }
  }
  __syncthreads();
  griddep_wait();
  TL(4, 1, tid == 0);
  griddep_launch();
  {
    const int cc = tid & 63;
    float sc[8], sh[8];
#pragma unroll
    for (int j = 0; j < 8; j++) {
      sc[j] = bf16_round(1.0f + g_mod[D_ + cc * 8 + j]);
      sh[j] = g_mod[cc * 8 + j];
    }
    for (int row = tid >> 6; row < 128; row += 6) {
      uint4* p = reinterpret_cast<uint4*>(sA + (cc >> 3) * 16384 + row * 128 + (((cc & 7) ^ (row & 7)) << 4));
      uint4 v = *p;
      uint32_t* u = reinterpret_cast<uint32_t*>(&v);
#pragma unroll
      for (int j = 0; j < 4; j++) {
        float2 a = unpack_bf16(u[j]);
        u[j] = pack_bf16(a.x * sc[2 * j] + sh[2 * j], a.y * sc[2 * j + 1] + sh[2 * j + 1]);
      }
      *p = v;
    }
  }
  fence_proxy_async();
  __syncthreads();
  TL(5, 0, tid == 0);

  if (warp < 4) {
    if (tid == 0) {
      for (int kt = G1_STAGES; kt < KT; kt++) {
        const int s = kt % G1_STAGES;
        mbar_wait(empty0 + 8 * s, ((kt / G1_STAGES) - 1) & 1);
        issue_b(kt, s);
      }
    }
  } else {
    const int wg = (warp >> 2) - 1;
    float acc[64];
#pragma unroll
    for (int i = 0; i < 64; i++) acc[i] = 0.f;
    const uint32_t a_base = smem_u32(sA) + wg * 8192;
    for (int kt = 0; kt < KT; kt++) {
      const int s = kt % G1_STAGES;
      mbar_wait(full0 + 8 * s, (kt / G1_STAGES) & 1);
      wgmma_fence();
      const uint32_t bs = smem_u32(sB + s * G1_STAGE_BYTES);
#pragma unroll
      for (int k = 0; k < 4; k++) {
        const uint64_t da = desc_sw128(a_base + kt * 16384 + k * 32, 16, 1024);
        const uint64_t db = desc_sw128(bs + k * 32, 16, 1024);
        wgmma_n128<0, 1>(acc, da, db, 1);
      }
      wgmma_commit();
      wgmma_wait<1>();
      if (kt > 0 && lane == 0) mbar_arrive(empty0 + 8 * ((kt - 1) % G1_STAGES));
    }
    wgmma_wait<0>();
    named_bar_sync(1, 256);
    TL(5, 1, tid == 128);
    constexpr int LDS = 128 * 2 + 16;
    uint8_t* st = sA + (warp - 4) * (16 * LDS);
    {
      const int r = lane >> 2, cq = (lane & 3) * 2;
#pragma unroll
      for (int j = 0; j < 16; j++) {
        *reinterpret_cast<uint32_t*>(st + r * LDS + (j * 8 + cq) * 2) = pack_bf16(acc[4 * j], acc[4 * j + 1]);
        *reinterpret_cast<uint32_t*>(st + (r + 8) * LDS + (j * 8 + cq) * 2) = pack_bf16(acc[4 * j + 2], acc[4 * j + 3]);
      }
    }
    __syncwarp();
    const int mrow = m0 + wg * 64 + (warp & 3) * 16;
#pragma unroll
    for (int i = 0; i < 8; i++) {
      const int r = i * 2 + (lane >> 4), ch = lane & 15;
      uint4 v = *reinterpret_cast<const uint4*>(st + r * LDS + ch * 16);
      *reinterpret_cast<uint4*>(out + (size_t)(mrow + r) * (2 * D_) + n0 + ch * 8) = v;
    }
    TL(6, 0, tid == 128); TL(6, 1, tid == 128);
  }
}

template <int MODE> struct GCfg;
template <> struct GCfg<0> { static constexpr int BN = 128, NBOX = 2, KT = 32, CM = 1, CN = 4, CK = 2, STAGES = 4; };
template <> struct GCfg<1> { static constexpr int BN = 176, NBOX = 3, KT = 8, CM = 2, CN = 4, CK = 1, STAGES = 4; };
template <> struct GCfg<2> { static constexpr int BN = 128, NBOX = 2, KT = 11, CM = 1, CN = 4, CK = 2, STAGES = 4; };

template <int MODE> constexpr int g_stage_bytes() { return 16384 + GCfg<MODE>::NBOX * 8192; }
constexpr int G_XCH_BYTES = 32768;
constexpr int G_STAT_BYTES = 8192;
template <int MODE> constexpr int g_smem_bytes() {
  return GCfg<MODE>::STAGES * g_stage_bytes<MODE>() + (GCfg<MODE>::CK > 1 ? G_XCH_BYTES : 0) + (MODE == 0 ? G_STAT_BYTES : 0) + 256;
}

template <int MODE>
__global__ void __cluster_dims__(8, 1, 1) __launch_bounds__(384, 1)
k_gemm(const __grid_constant__ CUtensorMap mapA0, const __grid_constant__ CUtensorMap mapA1,
       const __grid_constant__ CUtensorMap mapB, const __nv_bfloat16* __restrict__ res,
       __nv_bfloat16* __restrict__ out, __nv_bfloat16* __restrict__ out2) {
  using C = GCfg<MODE>;
  constexpr int BN = C::BN, KT = C::KT, CM = C::CM, CN = C::CN, CK = C::CK, STAGES = C::STAGES;
  constexpr int STAGE_BYTES = 16384 + C::NBOX * 8192;
  constexpr int NDEST = CN + CM - 1;
  extern __shared__ __align__(1024) uint8_t smem[];
  uint8_t* sStage = smem;
  uint8_t* sX = smem + STAGES * STAGE_BYTES;
  uint8_t* sStat = sX + (CK > 1 ? G_XCH_BYTES : 0);
  uint64_t* bars = reinterpret_cast<uint64_t*>(sStat + (MODE == 0 ? G_STAT_BYTES : 0));
  const uint32_t full0 = smem_u32(bars), empty0 = smem_u32(bars + STAGES);

  const int tid = threadIdx.x, warp = tid >> 5, lane = tid & 31;
  const int rank = blockIdx.x;
  const int cn = rank % CN, cm = (rank / CN) % CM, ck = rank / (CN * CM);
  int mt, nt;
  if (MODE == 1) { mt = (blockIdx.y >> 1) * 2 + cm; nt = (blockIdx.y & 1) * 4 + cn; }
  else { mt = blockIdx.y; nt = cn; }
  const int m0 = mt * 128, n0 = nt * BN;
  TL(8 + MODE * 4, 0, tid == 0);

  if (tid == 0) {
    for (int s = 0; s < STAGES; s++) { mbar_init(full0 + 8 * s, 1); mbar_init(empty0 + 8 * s, 8 * NDEST); }
    asm volatile("fence.mbarrier_init.release.cluster;" ::: "memory");
    fence_proxy_async();
  }
  __syncthreads();
  cluster_sync_all();
  griddep_wait();
  TL(8 + MODE * 4, 1, tid == 0);
  griddep_launch();

  if (warp < 4) {
    if (tid == 0) {
      const CUtensorMap* mapA = (MODE == 0 && ck) ? &mapA1 : &mapA0;
      const int kbase = (MODE == 2) ? ck * 11 * 64 : 0;
      const int nb = (MODE == 0) ? n0 + ck * 512 : n0;
      const uint16_t maskA = (uint16_t)(((1u << CN) - 1) << ((ck * CM + cm) * CN));
      uint16_t maskB = 0;
#pragma unroll
      for (int i = 0; i < CM; i++) maskB |= (uint16_t)(1u << ((ck * CM + i) * CN + cn));
      constexpr int AROWS = 128 / CN, BROWS = 64 / CM;
      for (int kt = 0; kt < KT; kt++) {
        const int s = kt % STAGES;
        if (kt >= STAGES) mbar_wait(empty0 + 8 * s, ((kt / STAGES) - 1) & 1);
        const uint32_t bar = full0 + 8 * s;
        const uint32_t dst = smem_u32(sStage + s * STAGE_BYTES);
        mbar_expect_tx(bar, STAGE_BYTES);
        const int k0 = kbase + kt * 64;
        tma_load_2d_mc(dst + cn * AROWS * 128, mapA, k0, m0 + cn * AROWS, bar, maskA);
#pragma unroll
        for (int j = 0; j < C::NBOX; j++) {
          if (CM > 1) tma_load_2d_mc(dst + 16384 + j * 8192 + cm * BROWS * 128, &mapB, nb + j * 64, k0 + cm * BROWS, bar, maskB);
          else tma_load_2d(dst + 16384 + j * 8192, &mapB, nb + j * 64, k0, bar);
        }
      }
    }
    __syncwarp();
    cluster_sync_all();
    if (MODE == 0) cluster_sync_all();
  } else {
    const int wg = (warp >> 2) - 1;
    float acc[BN / 2];
#pragma unroll
    for (int i = 0; i < BN / 2; i++) acc[i] = 0.f;
    int dest = -1;
    if (lane < CN) dest = (ck * CM + cm) * CN + lane;
    else if (lane < NDEST) {
      int o = lane - CN;
      int cmo = o + (o >= cm ? 1 : 0);
      dest = (ck * CM + cmo) * CN + cn;
    }
    for (int kt = 0; kt < KT; kt++) {
      const int s = kt % STAGES;
      mbar_wait(full0 + 8 * s, (kt / STAGES) & 1);
      wgmma_fence();
      const uint32_t as = smem_u32(sStage + s * STAGE_BYTES) + wg * 8192;
      const uint32_t bs = smem_u32(sStage + s * STAGE_BYTES) + 16384;
#pragma unroll
      for (int k = 0; k < 4; k++) {
        const uint64_t da = desc_sw128(as + k * 32, 16, 1024);
        const uint64_t db = desc_sw128(bs + k * 2048, 8192, 1024);
        if (BN == 128) wgmma_n128<1, 1>(*reinterpret_cast<float(*)[64]>(acc), da, db, 1);
        else wgmma_n176<1, 1>(*reinterpret_cast<float(*)[88]>(acc), da, db, 1);
      }
      wgmma_commit();
      wgmma_wait<1>();
      if (kt > 0 && dest >= 0) mbar_arrive_remote(empty0 + 8 * ((kt - 1) % STAGES), dest);
    }
    wgmma_wait<0>();
    TL(9 + MODE * 4, 0, tid == 128);

    if (MODE == 1) {
      cluster_sync_all();
      constexpr int LDS = BN * 2 + 16;
      uint8_t* st = sStage + (warp - 4) * (16 * LDS);
      const int r = lane >> 2, cq = (lane & 3) * 2;
#pragma unroll
      for (int j = 0; j < BN / 8; j++) {
        *reinterpret_cast<uint32_t*>(st + r * LDS + (j * 8 + cq) * 2) = pack_bf16(fmaxf(acc[4 * j], 0.f), fmaxf(acc[4 * j + 1], 0.f));
        *reinterpret_cast<uint32_t*>(st + (r + 8) * LDS + (j * 8 + cq) * 2) = pack_bf16(fmaxf(acc[4 * j + 2], 0.f), fmaxf(acc[4 * j + 3], 0.f));
      }
      __syncwarp();
      constexpr int CH = BN / 8;
      const int mrow = m0 + wg * 64 + (warp & 3) * 16;
      for (int idx = lane; idx < 16 * CH; idx += 32) {
        const int rr = idx / CH, ch = idx % CH;
        if (n0 + ch * 8 < DFF_) {
          uint4 v = *reinterpret_cast<const uint4*>(st + rr * LDS + ch * 16);
          *reinterpret_cast<uint4*>(out + (size_t)(mrow + rr) * DFF_ + n0 + ch * 8) = v;
        }
      }
      TL(10 + MODE * 4, 0, tid == 128); TL(10 + MODE * 4, 1, tid == 128);
    } else {
      const int t = tid & 127;
      const int half = ck;
      {
        const uint32_t remote = mapa(smem_u32(sX), rank ^ 4);
#pragma unroll
        for (int i = 0; i < 8; i++) {
          asm volatile("st.shared::cluster.v4.f32 [%0], {%1, %2, %3, %4};" ::"r"(remote + ((wg * 8 + i) * 128 + t) * 16),
                       "f"(half ? acc[4 * i] : acc[32 + 4 * i]), "f"(half ? acc[4 * i + 1] : acc[32 + 4 * i + 1]),
                       "f"(half ? acc[4 * i + 2] : acc[32 + 4 * i + 2]), "f"(half ? acc[4 * i + 3] : acc[32 + 4 * i + 3])
                       : "memory");
        }
      }
      cluster_sync_all();
      TL(9 + MODE * 4, 1, tid == 128);
      constexpr int LDSF = 68;
      float* st = reinterpret_cast<float*>(sStage) + (warp - 4) * (16 * LDSF);
      {
        const int r = lane >> 2, cq = (lane & 3) * 2;
#pragma unroll
        for (int j = 0; j < 8; j++) {
          const float4 o = *reinterpret_cast<const float4*>(sX + ((wg * 8 + j) * 128 + t) * 16);
          float a0 = half ? acc[32 + 4 * j] : acc[4 * j], a1 = half ? acc[32 + 4 * j + 1] : acc[4 * j + 1];
          float a2 = half ? acc[32 + 4 * j + 2] : acc[4 * j + 2], a3 = half ? acc[32 + 4 * j + 3] : acc[4 * j + 3];
          float v0, v1, v2, v3;
          if (MODE == 0) {
            if (half == 0) { v0 = a0 - o.x; v1 = a1 - o.y; v2 = a2 - o.z; v3 = a3 - o.w; }
            else { v0 = o.x - a0; v1 = o.y - a1; v2 = o.z - a2; v3 = o.w - a3; }
          } else {
            v0 = a0 + o.x; v1 = a1 + o.y; v2 = a2 + o.z; v3 = a3 + o.w;
          }
          *reinterpret_cast<float2*>(st + r * LDSF + j * 8 + cq) = make_float2(v0, v1);
          *reinterpret_cast<float2*>(st + (r + 8) * LDSF + j * 8 + cq) = make_float2(v2, v3);
        }
      }
      __syncwarp();
      const float* gate = g_mod + (MODE == 0 ? 2 : 5) * D_;
      const int cbase = n0 + half * 64 + (lane & 7) * 8;
      float g[8];
#pragma unroll
      for (int j = 0; j < 8; j++) g[j] = gate[cbase + j];
      const int rloc = wg * 64 + (warp & 3) * 16;
      uint4 rv[4];
#pragma unroll
      for (int i = 0; i < 4; i++) rv[i] = *reinterpret_cast<const uint4*>(res + (size_t)(m0 + rloc + i * 4 + (lane >> 3)) * D_ + cbase);
      float xv[4][8];
#pragma unroll
      for (int i = 0; i < 4; i++) {
        const int rr = i * 4 + (lane >> 3);
        const float4 f0 = *reinterpret_cast<const float4*>(st + rr * LDSF + (lane & 7) * 8);
        const float4 f1 = *reinterpret_cast<const float4*>(st + rr * LDSF + (lane & 7) * 8 + 4);
        const uint32_t* ru = reinterpret_cast<const uint32_t*>(&rv[i]);
        float2 q;
        q = unpack_bf16(ru[0]); xv[i][0] = bf16_round(q.x + g[0] * f0.x); xv[i][1] = bf16_round(q.y + g[1] * f0.y);
        q = unpack_bf16(ru[1]); xv[i][2] = bf16_round(q.x + g[2] * f0.z); xv[i][3] = bf16_round(q.y + g[3] * f0.w);
        q = unpack_bf16(ru[2]); xv[i][4] = bf16_round(q.x + g[4] * f1.x); xv[i][5] = bf16_round(q.y + g[5] * f1.y);
        q = unpack_bf16(ru[3]); xv[i][6] = bf16_round(q.x + g[6] * f1.z); xv[i][7] = bf16_round(q.y + g[7] * f1.w);
        uint4 o;
        uint32_t* ou = reinterpret_cast<uint32_t*>(&o);
#pragma unroll
        for (int j = 0; j < 4; j++) ou[j] = pack_bf16(xv[i][2 * j], xv[i][2 * j + 1]);
        *reinterpret_cast<uint4*>(out + (size_t)(m0 + rloc + rr) * D_ + cbase) = o;
      }
      if (MODE == 0) {
        float pm[4], pq[4];
#pragma unroll
        for (int i = 0; i < 4; i++) {
          float s = 0.f;
#pragma unroll
          for (int j = 0; j < 8; j++) s += xv[i][j];
          pm[i] = s;
        }
#pragma unroll
        for (int o = 1; o < 8; o <<= 1)
#pragma unroll
          for (int i = 0; i < 4; i++) pm[i] += __shfl_xor_sync(0xffffffffu, pm[i], o);
#pragma unroll
        for (int i = 0; i < 4; i++) {
          pm[i] *= (1.0f / 64.0f);
          float s = 0.f;
#pragma unroll
          for (int j = 0; j < 8; j++) { float d = xv[i][j] - pm[i]; s += d * d; }
          pq[i] = s;
        }
#pragma unroll
        for (int o = 1; o < 8; o <<= 1)
#pragma unroll
          for (int i = 0; i < 4; i++) pq[i] += __shfl_xor_sync(0xffffffffu, pq[i], o);
        const int blk = cn * 2 + half;
        const uint32_t rstat = mapa(smem_u32(sStat), lane & 7);
#pragma unroll
        for (int i = 0; i < 4; i++) {
          const int row = rloc + i * 4 + (lane >> 3);
          asm volatile("st.shared::cluster.v2.f32 [%0], {%1, %2};" ::"r"(rstat + (blk * 128 + row) * 8), "f"(pm[i]), "f"(pq[i]) : "memory");
        }
        cluster_sync_all();
        const float* scl = g_mod + 4 * D_;
        const float* sft = g_mod + 3 * D_;
        float sc[8], sh[8];
#pragma unroll
        for (int j = 0; j < 8; j++) { sc[j] = bf16_round(1.0f + scl[cbase + j]); sh[j] = sft[cbase + j]; }
#pragma unroll
        for (int i = 0; i < 4; i++) {
          const int row = rloc + i * 4 + (lane >> 3);
          float2 p[8];
#pragma unroll
          for (int b = 0; b < 8; b++) p[b] = *reinterpret_cast<const float2*>(sStat + (b * 128 + row) * 8);
          float mean = 0.f;
#pragma unroll
          for (int b = 0; b < 8; b++) mean += p[b].x;
          mean *= 0.125f;
          float m2 = 0.f;
#pragma unroll
          for (int b = 0; b < 8; b++) { float d = p[b].x - mean; m2 += p[b].y + 64.0f * d * d; }
          const float rstd = rsqrtf(m2 * (1.0f / D_) + 1e-5f);
          uint4 o;
          uint32_t* ou = reinterpret_cast<uint32_t*>(&o);
#pragma unroll
          for (int j = 0; j < 4; j++)
            ou[j] = pack_bf16((xv[i][2 * j] - mean) * rstd * sc[2 * j] + sh[2 * j],
                              (xv[i][2 * j + 1] - mean) * rstd * sc[2 * j + 1] + sh[2 * j + 1]);
          *reinterpret_cast<uint4*>(out2 + (size_t)(m0 + row) * D_ + cbase) = o;
        }
      }
      TL(10 + MODE * 4, 0, tid == 128); TL(10 + MODE * 4, 1, tid == 128);
    }
  }
}

typedef CUresult (*PFN_encodeTiled_t)(CUtensorMap*, CUtensorMapDataType, cuuint32_t, void*, const cuuint64_t*,
                                      const cuuint64_t*, const cuuint32_t*, const cuuint32_t*, CUtensorMapInterleave,
                                      CUtensorMapSwizzle, CUtensorMapL2promotion, CUtensorMapFloatOOBfill);

CUtensorMap make_map(PFN_encodeTiled_t enc, const void* ptr, uint64_t inner, uint64_t outer, uint32_t box_inner,
                     uint32_t box_outer) {
  CUtensorMap m;
  cuuint64_t dims[2] = {inner, outer};
  cuuint64_t strides[1] = {inner * 2};
  cuuint32_t box[2] = {box_inner, box_outer};
  cuuint32_t es[2] = {1, 1};
  enc(&m, CU_TENSOR_MAP_DATA_TYPE_BFLOAT16, 2, const_cast<void*>(ptr), dims, strides, box, es,
      CU_TENSOR_MAP_INTERLEAVE_NONE, CU_TENSOR_MAP_SWIZZLE_128B, CU_TENSOR_MAP_L2_PROMOTION_L2_256B,
      CU_TENSOR_MAP_FLOAT_OOB_FILL_NONE);
  return m;
}

template <typename... KArgs, typename... Args>
void launch(void (*kern)(KArgs...), dim3 grid, dim3 block, size_t smem, bool pdl, Args... args) {
  cudaLaunchConfig_t cfg = {};
  cfg.gridDim = grid;
  cfg.blockDim = block;
  cfg.dynamicSmemBytes = smem;
  cfg.stream = cudaStreamPerThread;
  cudaLaunchAttribute at[1];
  at[0].id = cudaLaunchAttributeProgrammaticStreamSerialization;
  at[0].val.programmaticStreamSerializationAllowed = 1;
  cfg.attrs = at;
  cfg.numAttrs = pdl ? 1 : 0;
  cudaLaunchKernelEx(&cfg, kern, KArgs(args)...);
}

}

extern "C" void kernel_launch(void* const* d_in, const int* in_sizes, int n_in, void* d_out, int out_size) {
  const __nv_bfloat16* x = (const __nv_bfloat16*)d_in[0];
  const __nv_bfloat16* ws_re = (const __nv_bfloat16*)d_in[1];
  const __nv_bfloat16* ws_im = (const __nv_bfloat16*)d_in[2];
  const __nv_bfloat16* wd_re = (const __nv_bfloat16*)d_in[3];
  const __nv_bfloat16* wd_im = (const __nv_bfloat16*)d_in[4];
  const __nv_bfloat16* w1 = (const __nv_bfloat16*)d_in[6];
  const __nv_bfloat16* w2 = (const __nv_bfloat16*)d_in[7];
  const __nv_bfloat16* c = (const __nv_bfloat16*)d_in[8];
  const __nv_bfloat16* w_mod = (const __nv_bfloat16*)d_in[9];
  __nv_bfloat16* out = (__nv_bfloat16*)d_out;

  void* fn = nullptr;
  cudaDriverEntryPointQueryResult qres;
  cudaGetDriverEntryPoint("cuTensorMapEncodeTiled", &fn, cudaEnableDefault, &qres);
  PFN_encodeTiled_t enc = (PFN_encodeTiled_t)fn;

  void *p_ab, *p_x1, *p_h1, *p_h2;
  cudaGetSymbolAddress(&p_ab, g_ab);
  cudaGetSymbolAddress(&p_x1, g_x1);
  cudaGetSymbolAddress(&p_h1, g_h1);
  cudaGetSymbolAddress(&p_h2, g_h2);

  const CUtensorMap m_wd_re = make_map(enc, wd_re, D_, D_, 64, 128);
  const CUtensorMap m_wd_im = make_map(enc, wd_im, D_, D_, 64, 128);
  const CUtensorMap m_ws_re = make_map(enc, ws_re, S_, S_, 64, 128 / GCfg<0>::CN);
  const CUtensorMap m_ws_im = make_map(enc, ws_im, S_, S_, 64, 128 / GCfg<0>::CN);
  const CUtensorMap m_ab = make_map(enc, p_ab, 2 * D_, S_, 64, 64 / GCfg<0>::CM);
  const CUtensorMap m_h2 = make_map(enc, p_h2, D_, S_, 64, 128 / GCfg<1>::CN);
  const CUtensorMap m_w1 = make_map(enc, w1, DFF_, D_, 64, 64 / GCfg<1>::CM);
  const CUtensorMap m_h1 = make_map(enc, p_h1, DFF_, S_, 64, 128 / GCfg<2>::CN);
  const CUtensorMap m_w2 = make_map(enc, w2, D_, DFF_, 64, 64 / GCfg<2>::CM);

  constexpr int SM_K1 = G1_A_BYTES + G1_STAGES * G1_STAGE_BYTES + 256;
  cudaFuncSetAttribute(k_gemm1, cudaFuncAttributeMaxDynamicSharedMemorySize, SM_K1);
  cudaFuncSetAttribute(k_gemm<0>, cudaFuncAttributeMaxDynamicSharedMemorySize, g_smem_bytes<0>());
  cudaFuncSetAttribute(k_gemm<1>, cudaFuncAttributeMaxDynamicSharedMemorySize, g_smem_bytes<1>());
  cudaFuncSetAttribute(k_gemm<2>, cudaFuncAttributeMaxDynamicSharedMemorySize, g_smem_bytes<2>());

  launch(k_mod, dim3(48), dim3(256), 0, false, c, w_mod);
  launch(k_gemm1, dim3(8, 16), dim3(384), SM_K1, true, m_wd_re, m_wd_im, x, (__nv_bfloat16*)p_ab);
  launch(k_gemm<0>, dim3(8, 16), dim3(384), g_smem_bytes<0>(), true, m_ws_re, m_ws_im, m_ab, x, (__nv_bfloat16*)p_x1,
         (__nv_bfloat16*)p_h2);
  launch(k_gemm<1>, dim3(8, 16), dim3(384), g_smem_bytes<1>(), true, m_h2, m_h2, m_w1, (const __nv_bfloat16*)nullptr,
         (__nv_bfloat16*)p_h1, (__nv_bfloat16*)nullptr);
  launch(k_gemm<2>, dim3(8, 16), dim3(384), g_smem_bytes<2>(), true, m_h1, m_h1, m_w2, (const __nv_bfloat16*)p_x1, out,
         (__nv_bfloat16*)nullptr);
}
```

```cpp
#include <cuda_runtime.h>
#include <cuda_bf16.h>
#include <cuda.h>
#include <stdint.h>

namespace {

constexpr int S_ = 2048, D_ = 512, DFF_ = 1376;

__device__ __align__(1024) float          g_mod[6 * D_];
__device__ __align__(1024) float          g_uv[2 * 1408];
__device__ __align__(1024) float2         g_stat[S_ * 8];
__device__ __align__(1024) __nv_bfloat16  g_ab[S_ * 2 * D_];
__device__ __align__(1024) __nv_bfloat16  g_x1[S_ * D_];
__device__ __align__(1024) __nv_bfloat16  g_x1s[S_ * D_];
__device__ __align__(1024) __nv_bfloat16  g_h1[S_ * DFF_];

#define TL(slot, which, cond)

__device__ __forceinline__ uint32_t smem_u32(const void* p) { return (uint32_t)__cvta_generic_to_shared(p); }

__device__ __forceinline__ void mbar_init(uint32_t bar, uint32_t count) {
  asm volatile("mbarrier.init.shared::cta.b64 [%0], %1;" ::"r"(bar), "r"(count) : "memory");
}
__device__ __forceinline__ void mbar_expect_tx(uint32_t bar, uint32_t bytes) {
  asm volatile("mbarrier.arrive.expect_tx.shared::cta.b64 _, [%0], %1;" ::"r"(bar), "r"(bytes) : "memory");
}
__device__ __forceinline__ void mbar_arrive(uint32_t bar) {
  asm volatile("mbarrier.arrive.shared::cta.b64 _, [%0];" ::"r"(bar) : "memory");
}
__device__ __forceinline__ uint32_t mapa(uint32_t addr, uint32_t rank) {
  uint32_t r;
  asm volatile("mapa.shared::cluster.u32 %0, %1, %2;" : "=r"(r) : "r"(addr), "r"(rank));
  return r;
}
__device__ __forceinline__ void mbar_arrive_remote(uint32_t bar, uint32_t rank) {
  asm volatile("mbarrier.arrive.release.cluster.shared::cluster.b64 _, [%0];" ::"r"(mapa(bar, rank)) : "memory");
}
__device__ __forceinline__ bool mbar_try_wait(uint32_t bar, uint32_t parity) {
  uint32_t ok;
  asm volatile(
      "{\n.reg .pred p;\n"
      "mbarrier.try_wait.parity.shared::cta.b64 p, [%1], %2;\n"
      "selp.u32 %0, 1, 0, p;\n}\n"
      : "=r"(ok)
      : "r"(bar), "r"(parity)
      : "memory");
  return ok != 0;
}
__device__ __forceinline__ void mbar_wait(uint32_t bar, uint32_t parity) {
  uint32_t spins = 0;
  while (!mbar_try_wait(bar, parity)) {
    if (++spins > (1u << 24)) __trap();
  }
}
__device__ __forceinline__ void tma_load_2d(uint32_t dst, const CUtensorMap* map, int c0, int c1, uint32_t bar) {
  asm volatile(
      "cp.async.bulk.tensor.2d.shared::cluster.global.mbarrier::complete_tx::bytes [%0], [%1, {%3, %4}], [%2];"
      ::"r"(dst), "l"(map), "r"(bar), "r"(c0), "r"(c1)
      : "memory");
}
__device__ __forceinline__ void tma_load_2d_mc(uint32_t dst, const CUtensorMap* map, int c0, int c1, uint32_t bar,
                                               uint16_t mask) {
  asm volatile(
      "cp.async.bulk.tensor.2d.shared::cluster.global.mbarrier::complete_tx::bytes.multicast::cluster [%0], [%1, {%3, %4}], [%2], %5;"
      ::"r"(dst), "l"(map), "r"(bar), "r"(c0), "r"(c1), "h"(mask)
      : "memory");
}
__device__ __forceinline__ void wgmma_fence() { asm volatile("wgmma.fence.sync.aligned;" ::: "memory"); }
__device__ __forceinline__ void wgmma_commit() { asm volatile("wgmma.commit_group.sync.aligned;" ::: "memory"); }
template <int N>
__device__ __forceinline__ void wgmma_wait() { asm volatile("wgmma.wait_group.sync.aligned %0;" ::"n"(N) : "memory"); }
__device__ __forceinline__ void fence_proxy_async() { asm volatile("fence.proxy.async.shared::cta;" ::: "memory"); }
__device__ __forceinline__ void named_bar_sync(int id, int nthreads) {
  asm volatile("bar.sync %0, %1;" ::"r"(id), "r"(nthreads) : "memory");
}
__device__ __forceinline__ void griddep_wait() { asm volatile("griddepcontrol.wait;" ::: "memory"); }
__device__ __forceinline__ void griddep_launch() { asm volatile("griddepcontrol.launch_dependents;" ::: "memory"); }
__device__ __forceinline__ void cluster_sync_all() {
  asm volatile("barrier.cluster.arrive.release.aligned;\nbarrier.cluster.wait.acquire.aligned;" ::: "memory");
}

__device__ __forceinline__ uint64_t desc_sw128(uint32_t addr, uint32_t lbo_bytes, uint32_t sbo_bytes) {
  uint64_t d = 0;
  d |= (uint64_t)((addr & 0x3FFFF) >> 4);
  d |= (uint64_t)((lbo_bytes & 0x3FFFF) >> 4) << 16;
  d |= (uint64_t)((sbo_bytes & 0x3FFFF) >> 4) << 32;
  d |= (uint64_t)1 << 62;
  return d;
}

template <int TNSPB, int SCALEA>
__device__ __forceinline__ void wgmma_n128(float (&d)[64], uint64_t da, uint64_t db, int scaleD) {
  asm volatile("{\n.reg .pred p;\nsetp.ne.b32 p, %66, 0;\n"
    "wgmma.mma_async.sync.aligned.m64n128k16.f32.bf16.bf16 {%0, %1, %2, %3, %4, %5, %6, %7, %8, %9, %10, %11, %12, %13, %14, %15, %16, %17, %18, %19, %20, %21, %22, %23, %24, %25, %26, %27, %28, %29, %30, %31, %32, %33, %34, %35, %36, %37, %38, %39, %40, %41, %42, %43, %44, %45, %46, %47, %48, %49, %50, %51, %52, %53, %54, %55, %56, %57, %58, %59, %60, %61, %62, %63}, %64, %65, p, %68, 1, 0, %67;\n}\n"
    : "+f"(d[0]), "+f"(d[1]), "+f"(d[2]), "+f"(d[3]), "+f"(d[4]), "+f"(d[5]), "+f"(d[6]), "+f"(d[7]), "+f"(d[8]), "+f"(d[9]), "+f"(d[10]), "+f"(d[11]), "+f"(d[12]), "+f"(d[13]), "+f"(d[14]), "+f"(d[15]), "+f"(d[16]), "+f"(d[17]), "+f"(d[18]), "+f"(d[19]), "+f"(d[20]), "+f"(d[21]), "+f"(d[22]), "+f"(d[23]), "+f"(d[24]), "+f"(d[25]), "+f"(d[26]), "+f"(d[27]), "+f"(d[28]), "+f"(d[29]), "+f"(d[30]), "+f"(d[31]), "+f"(d[32]), "+f"(d[33]), "+f"(d[34]), "+f"(d[35]), "+f"(d[36]), "+f"(d[37]), "+f"(d[38]), "+f"(d[39]), "+f"(d[40]), "+f"(d[41]), "+f"(d[42]), "+f"(d[43]), "+f"(d[44]), "+f"(d[45]), "+f"(d[46]), "+f"(d[47]), "+f"(d[48]), "+f"(d[49]), "+f"(d[50]), "+f"(d[51]), "+f"(d[52]), "+f"(d[53]), "+f"(d[54]), "+f"(d[55]), "+f"(d[56]), "+f"(d[57]), "+f"(d[58]), "+f"(d[59]), "+f"(d[60]), "+f"(d[61]), "+f"(d[62]), "+f"(d[63])
    : "l"(da), "l"(db), "r"(scaleD), "n"(TNSPB), "n"(SCALEA));
}

template <int TNSPB, int SCALEA>
__device__ __forceinline__ void wgmma_n176(float (&d)[88], uint64_t da, uint64_t db, int scaleD) {
  asm volatile("{\n.reg .pred p;\nsetp.ne.b32 p, %90, 0;\n"
    "wgmma.mma_async.sync.aligned.m64n176k16.f32.bf16.bf16 {%0, %1, %2, %3, %4, %5, %6, %7, %8, %9, %10, %11, %12, %13, %14, %15, %16, %17, %18, %19, %20, %21, %22, %23, %24, %25, %26, %27, %28, %29, %30, %31, %32, %33, %34, %35, %36, %37, %38, %39, %40, %41, %42, %43, %44, %45, %46, %47, %48, %49, %50, %51, %52, %53, %54, %55, %56, %57, %58, %59, %60, %61, %62, %63, %64, %65, %66, %67, %68, %69, %70, %71, %72, %73, %74, %75, %76, %77, %78, %79, %80, %81, %82, %83, %84, %85, %86, %87}, %88, %89, p, %92, 1, 0, %91;\n}\n"
    : "+f"(d[0]), "+f"(d[1]), "+f"(d[2]), "+f"(d[3]), "+f"(d[4]), "+f"(d[5]), "+f"(d[6]), "+f"(d[7]), "+f"(d[8]), "+f"(d[9]), "+f"(d[10]), "+f"(d[11]), "+f"(d[12]), "+f"(d[13]), "+f"(d[14]), "+f"(d[15]), "+f"(d[16]), "+f"(d[17]), "+f"(d[18]), "+f"(d[19]), "+f"(d[20]), "+f"(d[21]), "+f"(d[22]), "+f"(d[23]), "+f"(d[24]), "+f"(d[25]), "+f"(d[26]), "+f"(d[27]), "+f"(d[28]), "+f"(d[29]), "+f"(d[30]), "+f"(d[31]), "+f"(d[32]), "+f"(d[33]), "+f"(d[34]), "+f"(d[35]), "+f"(d[36]), "+f"(d[37]), "+f"(d[38]), "+f"(d[39]), "+f"(d[40]), "+f"(d[41]), "+f"(d[42]), "+f"(d[43]), "+f"(d[44]), "+f"(d[45]), "+f"(d[46]), "+f"(d[47]), "+f"(d[48]), "+f"(d[49]), "+f"(d[50]), "+f"(d[51]), "+f"(d[52]), "+f"(d[53]), "+f"(d[54]), "+f"(d[55]), "+f"(d[56]), "+f"(d[57]), "+f"(d[58]), "+f"(d[59]), "+f"(d[60]), "+f"(d[61]), "+f"(d[62]), "+f"(d[63]), "+f"(d[64]), "+f"(d[65]), "+f"(d[66]), "+f"(d[67]), "+f"(d[68]), "+f"(d[69]), "+f"(d[70]), "+f"(d[71]), "+f"(d[72]), "+f"(d[73]), "+f"(d[74]), "+f"(d[75]), "+f"(d[76]), "+f"(d[77]), "+f"(d[78]), "+f"(d[79]), "+f"(d[80]), "+f"(d[81]), "+f"(d[82]), "+f"(d[83]), "+f"(d[84]), "+f"(d[85]), "+f"(d[86]), "+f"(d[87])
    : "l"(da), "l"(db), "r"(scaleD), "n"(TNSPB), "n"(SCALEA));
}

__device__ __forceinline__ float bf16_round(float v) { return __bfloat162float(__float2bfloat16(v)); }
__device__ __forceinline__ uint32_t pack_bf16(float lo, float hi) {
  __nv_bfloat162 t = __floats2bfloat162_rn(lo, hi);
  return *reinterpret_cast<uint32_t*>(&t);
}
__device__ __forceinline__ float2 unpack_bf16(uint32_t u) {
  __nv_bfloat162 t = *reinterpret_cast<__nv_bfloat162*>(&u);
  return __bfloat1622float2(t);
}

__global__ void __launch_bounds__(256) k_mod(const __nv_bfloat16* __restrict__ c, const __nv_bfloat16* __restrict__ w_mod) {
  __shared__ float red[32][65];
  __shared__ float sc[D_];
  TL(0, 0, threadIdx.x == 0);
  griddep_launch();
  const int tx = threadIdx.x & 7, ty = threadIdx.x >> 3;
  const int col = blockIdx.x * 64 + tx * 8;
  uint4 v[16];
#pragma unroll
  for (int r = 0; r < 16; r++) v[r] = __ldg(reinterpret_cast<const uint4*>(w_mod + (size_t)(ty * 16 + r) * (6 * D_) + col));
  for (int i = threadIdx.x; i < D_; i += 256) {
    float x = __bfloat162float(c[i]);
    sc[i] = bf16_round(x / (1.0f + __expf(-x)));
  }
  __syncthreads();
  float acc[8];
#pragma unroll
  for (int j = 0; j < 8; j++) acc[j] = 0.f;
#pragma unroll
  for (int r = 0; r < 16; r++) {
    float s = sc[ty * 16 + r];
    const uint32_t* u = reinterpret_cast<const uint32_t*>(&v[r]);
#pragma unroll
    for (int j = 0; j < 4; j++) {
      float2 f = unpack_bf16(u[j]);
      acc[2 * j] += s * f.x;
      acc[2 * j + 1] += s * f.y;
    }
  }
#pragma unroll
  for (int j = 0; j < 8; j++) red[ty][tx * 8 + j] = acc[j];
  __syncthreads();
  if (threadIdx.x < 64) {
    float s = 0.f;
#pragma unroll
    for (int r = 0; r < 32; r++) s += red[r][threadIdx.x];
    g_mod[blockIdx.x * 64 + threadIdx.x] = bf16_round(s);
  }
  TL(0, 1, threadIdx.x == 0);
}

constexpr int G1_A_BYTES = 128 * 512 * 2;
constexpr int G1_STAGES = 4;
constexpr int G1_STAGE_BYTES = 16384;

__global__ void __launch_bounds__(384, 1)
k_gemm1(const __grid_constant__ CUtensorMap mapB0, const __grid_constant__ CUtensorMap mapB1,
        const __nv_bfloat16* __restrict__ xin, const __nv_bfloat16* __restrict__ w1, __nv_bfloat16* __restrict__ out) {
  constexpr int KT = 8;
  extern __shared__ __align__(1024) uint8_t smem[];
  const int tid = threadIdx.x, warp = tid >> 5, lane = tid & 31;

  if (blockIdx.x >= 128) {
    griddep_wait();
    griddep_launch();
    float* sk = reinterpret_cast<float*>(smem);
    float* red = sk + 1024;
    for (int i = tid; i < D_; i += 384) {
      sk[i] = bf16_round(1.0f + g_mod[4 * D_ + i]);
      sk[D_ + i] = g_mod[3 * D_ + i];
    }
    __syncthreads();
    const int c0 = (blockIdx.x - 128) * 344;
    const int cg = tid % 43, kg = tid / 43;
    if (kg < 8) {
      float u[8], v[8];
#pragma unroll
      for (int j = 0; j < 8; j++) { u[j] = 0.f; v[j] = 0.f; }
#pragma unroll 4
      for (int r = 0; r < 64; r++) {
        const int k = kg * 64 + r;
        const uint4 w = __ldg(reinterpret_cast<const uint4*>(w1 + (size_t)k * DFF_ + c0 + cg * 8));
        const uint32_t* wu = reinterpret_cast<const uint32_t*>(&w);
        const float a = sk[k], b = sk[D_ + k];
#pragma unroll
        for (int j = 0; j < 4; j++) {
          float2 f = unpack_bf16(wu[j]);
          u[2 * j] += a * f.x; u[2 * j + 1] += a * f.y;
          v[2 * j] += b * f.x; v[2 * j + 1] += b * f.y;
        }
      }
#pragma unroll
      for (int j = 0; j < 8; j++) {
        red[(kg * 344 + cg * 8 + j) * 2] = u[j];
        red[(kg * 344 + cg * 8 + j) * 2 + 1] = v[j];
      }
    }
    __syncthreads();
    if (tid < 344) {
      float u = 0.f, v = 0.f;
#pragma unroll
      for (int g = 0; g < 8; g++) { u += red[(g * 344 + tid) * 2]; v += red[(g * 344 + tid) * 2 + 1]; }
      g_uv[2 * (c0 + tid)] = u;
      g_uv[2 * (c0 + tid) + 1] = v;
    }
    return;
  }

  uint8_t* sA = smem;
  uint8_t* sB = smem + G1_A_BYTES;
  uint64_t* bars = reinterpret_cast<uint64_t*>(smem + G1_A_BYTES + G1_STAGES * G1_STAGE_BYTES);
  const uint32_t full0 = smem_u32(bars), empty0 = smem_u32(bars + G1_STAGES);
  const int m0 = (blockIdx.x >> 3) * 128, n0 = (blockIdx.x & 7) * 128;
  TL(4, 0, tid == 0);
  const CUtensorMap* mapB = n0 >= 512 ? &mapB1 : &mapB0;
  const int nb = n0 & 511;

  if (tid == 0) {
    for (int s = 0; s < G1_STAGES; s++) { mbar_init(full0 + 8 * s, 1); mbar_init(empty0 + 8 * s, 8); }
    asm volatile("fence.mbarrier_init.release.cluster;" ::: "memory");
    fence_proxy_async();
  }
  __syncthreads();

  auto issue_b = [&](int kt, int s) {
    const uint32_t bar = full0 + 8 * s;
    mbar_expect_tx(bar, G1_STAGE_BYTES);
    tma_load_2d(smem_u32(sB + s * G1_STAGE_BYTES), mapB, kt * 64, nb, bar);
  };
  if (tid == 0) {
    for (int s = 0; s < G1_STAGES; s++) issue_b(s, s);
  }

  for (int base = warp * 4; base < 128; base += 48) {
    uint4 v0[4], v1[4];
#pragma unroll
    for (int i = 0; i < 4; i++) {
      const uint4* src = reinterpret_cast<const uint4*>(xin + (size_t)(m0 + base + i) * D_);
      v0[i] = src[lane];
      v1[i] = src[lane + 32];
    }
    float f[4][16], s[4], q[4];
#pragma unroll
    for (int i = 0; i < 4; i++) {
      const uint32_t* u0 = reinterpret_cast<const uint32_t*>(&v0[i]);
      const uint32_t* u1 = reinterpret_cast<const uint32_t*>(&v1[i]);
      s[i] = 0.f;
#pragma unroll
      for (int j = 0; j < 4; j++) {
        float2 a = unpack_bf16(u0[j]), b = unpack_bf16(u1[j]);
        f[i][2 * j] = a.x; f[i][2 * j + 1] = a.y; f[i][8 + 2 * j] = b.x; f[i][8 + 2 * j + 1] = b.y;
        s[i] += (a.x + a.y) + (b.x + b.y);
      }
    }
#pragma unroll
    for (int o = 16; o > 0; o >>= 1)
#pragma unroll
      for (int i = 0; i < 4; i++) s[i] += __shfl_xor_sync(0xffffffffu, s[i], o);
#pragma unroll
    for (int i = 0; i < 4; i++) {
      const float mean = s[i] * (1.0f / D_);
      q[i] = 0.f;
#pragma unroll
      for (int j = 0; j < 16; j++) { f[i][j] -= mean; q[i] += f[i][j] * f[i][j]; }
    }
#pragma unroll
    for (int o = 16; o > 0; o >>= 1)
#pragma unroll
      for (int i = 0; i < 4; i++) q[i] += __shfl_xor_sync(0xffffffffu, q[i], o);
#pragma unroll
    for (int i = 0; i < 4; i++) {
      const int row = base + i;
      const float rstd = rsqrtf(q[i] * (1.0f / D_) + 1e-5f);
      uint4 o0, o1;
      uint32_t* p0 = reinterpret_cast<uint32_t*>(&o0);
      uint32_t* p1 = reinterpret_cast<uint32_t*>(&o1);
#pragma unroll
      for (int j = 0; j < 4; j++) {
        p0[j] = pack_bf16(f[i][2 * j] * rstd, f[i][2 * j + 1] * rstd);
        p1[j] = pack_bf16(f[i][8 + 2 * j] * rstd, f[i][8 + 2 * j + 1] * rstd);
      }
      const int c0 = lane, c1 = lane + 32;
      *reinterpret_cast<uint4*>(sA + (c0 >> 3) * 16384 + row * 128 + (((c0 & 7) ^ (row & 7)) << 4)) = o0;
      *reinterpret_cast<uint4*>(sA + (c1 >> 3) * 16384 + row * 128 + (((c1 & 7) ^ (row & 7)) << 4)) = o1;
    }
  }
  __syncthreads();
  griddep_wait();
  TL(4, 1, tid == 0);
  griddep_launch();
  {
    const int cc = tid & 63;
    float sc[8], sh[8];
    {
      const float4 a0 = *reinterpret_cast<const float4*>(g_mod + D_ + cc * 8), a1 = *reinterpret_cast<const float4*>(g_mod + D_ + cc * 8 + 4);
      const float4 b0 = *reinterpret_cast<const float4*>(g_mod + cc * 8), b1 = *reinterpret_cast<const float4*>(g_mod + cc * 8 + 4);
      sc[0] = bf16_round(1.f + a0.x); sc[1] = bf16_round(1.f + a0.y); sc[2] = bf16_round(1.f + a0.z); sc[3] = bf16_round(1.f + a0.w);
      sc[4] = bf16_round(1.f + a1.x); sc[5] = bf16_round(1.f + a1.y); sc[6] = bf16_round(1.f + a1.z); sc[7] = bf16_round(1.f + a1.w);
      sh[0] = b0.x; sh[1] = b0.y; sh[2] = b0.z; sh[3] = b0.w; sh[4] = b1.x; sh[5] = b1.y; sh[6] = b1.z; sh[7] = b1.w;
    }
#pragma unroll 2
    for (int row = tid >> 6; row < 128; row += 6) {
      uint4* p = reinterpret_cast<uint4*>(sA + (cc >> 3) * 16384 + row * 128 + (((cc & 7) ^ (row & 7)) << 4));
      uint4 v = *p;
      uint32_t* u = reinterpret_cast<uint32_t*>(&v);
#pragma unroll
      for (int j = 0; j < 4; j++) {
        float2 a = unpack_bf16(u[j]);
        u[j] = pack_bf16(a.x * sc[2 * j] + sh[2 * j], a.y * sc[2 * j + 1] + sh[2 * j + 1]);
      }
      *p = v;
    }
  }
  fence_proxy_async();
  __syncthreads();
  TL(5, 0, tid == 0);

  if (warp < 4) {
    if (tid == 0) {
      for (int kt = G1_STAGES; kt < KT; kt++) {
        const int s = kt % G1_STAGES;
        mbar_wait(empty0 + 8 * s, ((kt / G1_STAGES) - 1) & 1);
        issue_b(kt, s);
      }
    }
  } else {
    const int wg = (warp >> 2) - 1;
    float acc[64];
#pragma unroll
    for (int i = 0; i < 64; i++) acc[i] = 0.f;
    const uint32_t a_base = smem_u32(sA) + wg * 8192;
    for (int kt = 0; kt < KT; kt++) {
      const int s = kt % G1_STAGES;
      mbar_wait(full0 + 8 * s, (kt / G1_STAGES) & 1);
      wgmma_fence();
      const uint32_t bs = smem_u32(sB + s * G1_STAGE_BYTES);
#pragma unroll
      for (int k = 0; k < 4; k++) {
        const uint64_t da = desc_sw128(a_base + kt * 16384 + k * 32, 16, 1024);
        const uint64_t db = desc_sw128(bs + k * 32, 16, 1024);
        wgmma_n128<0, 1>(acc, da, db, 1);
      }
      wgmma_commit();
      wgmma_wait<1>();
      if (kt > 0 && lane == 0) mbar_arrive(empty0 + 8 * ((kt - 1) % G1_STAGES));
    }
    wgmma_wait<0>();
    named_bar_sync(1, 256);
    TL(5, 1, tid == 128);
    constexpr int LDS = 128 * 2 + 16;
    uint8_t* st = sA + (warp - 4) * (16 * LDS);
    {
      const int r = lane >> 2, cq = (lane & 3) * 2;
#pragma unroll
      for (int j = 0; j < 16; j++) {
        *reinterpret_cast<uint32_t*>(st + r * LDS + (j * 8 + cq) * 2) = pack_bf16(acc[4 * j], acc[4 * j + 1]);
        *reinterpret_cast<uint32_t*>(st + (r + 8) * LDS + (j * 8 + cq) * 2) = pack_bf16(acc[4 * j + 2], acc[4 * j + 3]);
      }
    }
    __syncwarp();
    const int mrow = m0 + wg * 64 + (warp & 3) * 16;
#pragma unroll
    for (int i = 0; i < 8; i++) {
      const int r = i * 2 + (lane >> 4), ch = lane & 15;
      uint4 v = *reinterpret_cast<const uint4*>(st + r * LDS + ch * 16);
      *reinterpret_cast<uint4*>(out + (size_t)(mrow + r) * (2 * D_) + n0 + ch * 8) = v;
    }
    TL(6, 0, tid == 128); TL(6, 1, tid == 128);
  }
}

template <int MODE> struct GCfg;
template <> struct GCfg<0> { static constexpr int BN = 128, NBOX = 2, KT = 32, STAGES = 4; };
template <> struct GCfg<1> { static constexpr int BN = 176, NBOX = 3, KT = 8, STAGES = 4; };
template <> struct GCfg<2> { static constexpr int BN = 128, NBOX = 2, KT = 11, STAGES = 4; };

constexpr int G_XCH_BYTES = 32768;
template <int MODE> constexpr int g_smem_bytes() {
  return GCfg<MODE>::STAGES * (16384 + GCfg<MODE>::NBOX * 8192) + (MODE != 1 ? G_XCH_BYTES : 4096) + 256;
}

template <int MODE>
__global__ void __cluster_dims__(2, 1, 1) __launch_bounds__(384, 1)
k_gemm(const __grid_constant__ CUtensorMap mapA0, const __grid_constant__ CUtensorMap mapA1,
       const __grid_constant__ CUtensorMap mapB, const __nv_bfloat16* __restrict__ res,
       __nv_bfloat16* __restrict__ out, __nv_bfloat16* __restrict__ out2) {
  using C = GCfg<MODE>;
  constexpr int BN = C::BN, KT = C::KT, STAGES = C::STAGES;
  constexpr int STAGE_BYTES = 16384 + C::NBOX * 8192;
  constexpr bool MC = (MODE == 1);
  extern __shared__ __align__(1024) uint8_t smem[];
  uint8_t* sStage = smem;
  uint8_t* sX = smem + STAGES * STAGE_BYTES;
  uint64_t* bars = reinterpret_cast<uint64_t*>(sX + (MODE != 1 ? G_XCH_BYTES : 4096));
  const uint32_t full0 = smem_u32(bars), empty0 = smem_u32(bars + STAGES);

  const int tid = threadIdx.x, warp = tid >> 5, lane = tid & 31;
  const int rank = blockIdx.x & 1;
  int m0, n0;
  if (MODE == 1) { m0 = (blockIdx.y * 2 + rank) * 128; n0 = (blockIdx.x >> 1) * BN; }
  else { m0 = blockIdx.y * 128; n0 = (blockIdx.x >> 1) * BN; }
  TL(8 + MODE * 4, 0, tid == 0);

  if (tid == 0) {
    for (int s = 0; s < STAGES; s++) { mbar_init(full0 + 8 * s, 1); mbar_init(empty0 + 8 * s, MC ? 16 : 8); }
    asm volatile("fence.mbarrier_init.release.cluster;" ::: "memory");
    fence_proxy_async();
  }
  __syncthreads();
  if (MC) cluster_sync_all();
  griddep_wait();
  TL(8 + MODE * 4, 1, tid == 0);
  griddep_launch();

  if (warp < 4) {
    if (tid == 0) {
      const CUtensorMap* mapA = (MODE == 0 && rank) ? &mapA1 : &mapA0;
      const int kbase = (MODE == 2) ? rank * 11 * 64 : 0;
      const int nb = (MODE == 0) ? n0 + rank * 512 : n0;
      for (int kt = 0; kt < KT; kt++) {
        const int s = kt % STAGES;
        if (kt >= STAGES) mbar_wait(empty0 + 8 * s, ((kt / STAGES) - 1) & 1);
        const uint32_t bar = full0 + 8 * s;
        const uint32_t dst = smem_u32(sStage + s * STAGE_BYTES);
        mbar_expect_tx(bar, STAGE_BYTES);
        const int k0 = kbase + kt * 64;
        tma_load_2d(dst, mapA, k0, m0, bar);
#pragma unroll
        for (int j = 0; j < C::NBOX; j++) {
          if (MC) tma_load_2d_mc(dst + 16384 + j * 8192 + rank * 4096, &mapB, nb + j * 64, k0 + rank * 32, bar, (uint16_t)3);
          else tma_load_2d(dst + 16384 + j * 8192, &mapB, nb + j * 64, k0, bar);
        }
      }
    } else if (MODE == 1 && tid >= 32) {
      for (int row = tid - 32; row < 128; row += 96) {
        const float4* p = reinterpret_cast<const float4*>(g_stat + (size_t)(m0 + row) * 8);
        float mb[8], qb[8];
#pragma unroll
        for (int b = 0; b < 4; b++) { const float4 t4 = p[b]; mb[2 * b] = t4.x; qb[2 * b] = t4.y; mb[2 * b + 1] = t4.z; qb[2 * b + 1] = t4.w; }
        float mean = 0.f;
#pragma unroll
        for (int b = 0; b < 8; b++) mean += mb[b];
        mean *= 0.125f;
        float m2 = 0.f;
#pragma unroll
        for (int b = 0; b < 8; b++) { const float d = mb[b] - mean; m2 += qb[b] + 64.0f * d * d; }
        reinterpret_cast<float2*>(sX)[row] = make_float2(mean, rsqrtf(m2 * (1.0f / D_) + 1e-5f));
      }
    }
    __syncwarp();
    if (MODE == 1) named_bar_sync(2, 384);
    cluster_sync_all();
  } else {
    const int wg = (warp >> 2) - 1;
    float acc[BN / 2];
#pragma unroll
    for (int i = 0; i < BN / 2; i++) acc[i] = 0.f;
    for (int kt = 0; kt < KT; kt++) {
      const int s = kt % STAGES;
      mbar_wait(full0 + 8 * s, (kt / STAGES) & 1);
      wgmma_fence();
      const uint32_t as = smem_u32(sStage + s * STAGE_BYTES) + wg * 8192;
      const uint32_t bs = smem_u32(sStage + s * STAGE_BYTES) + 16384;
#pragma unroll
      for (int k = 0; k < 4; k++) {
        const uint64_t da = desc_sw128(as + k * 32, 16, 1024);
        const uint64_t db = desc_sw128(bs + k * 2048, 8192, 1024);
        if (BN == 128) wgmma_n128<1, 1>(*reinterpret_cast<float(*)[64]>(acc), da, db, 1);
        else wgmma_n176<1, 1>(*reinterpret_cast<float(*)[88]>(acc), da, db, 1);
      }
      wgmma_commit();
      wgmma_wait<1>();
      if (kt > 0) {
        if (MC) { if (lane < 2) mbar_arrive_remote(empty0 + 8 * ((kt - 1) % STAGES), lane); }
        else if (lane == 0) mbar_arrive(empty0 + 8 * ((kt - 1) % STAGES));
      }
    }
    wgmma_wait<0>();
    TL(9 + MODE * 4, 0, tid == 128);

    if (MODE == 1) {
      named_bar_sync(2, 384);
      const int r = lane >> 2, cq = (lane & 3) * 2;
      const int rl = wg * 64 + (warp & 3) * 16 + r;
      const float2 st0 = reinterpret_cast<const float2*>(sX)[rl], st1 = reinterpret_cast<const float2*>(sX)[rl + 8];
      cluster_sync_all();
      constexpr int LDS = BN * 2 + 16;
      uint8_t* st = sStage + (warp - 4) * (16 * LDS);
#pragma unroll
      for (int j = 0; j < BN / 8; j++) {
        const int col = n0 + j * 8 + cq;
        float4 uv = make_float4(0.f, 0.f, 0.f, 0.f);
        if (col < DFF_) uv = *reinterpret_cast<const float4*>(g_uv + 2 * col);
        const float v0 = fmaxf(st0.y * (acc[4 * j] - st0.x * uv.x) + uv.y, 0.f);
        const float v1 = fmaxf(st0.y * (acc[4 * j + 1] - st0.x * uv.z) + uv.w, 0.f);
        const float v2 = fmaxf(st1.y * (acc[4 * j + 2] - st1.x * uv.x) + uv.y, 0.f);
        const float v3 = fmaxf(st1.y * (acc[4 * j + 3] - st1.x * uv.z) + uv.w, 0.f);
        *reinterpret_cast<uint32_t*>(st + r * LDS + (j * 8 + cq) * 2) = pack_bf16(v0, v1);
        *reinterpret_cast<uint32_t*>(st + (r + 8) * LDS + (j * 8 + cq) * 2) = pack_bf16(v2, v3);
      }
      __syncwarp();
      constexpr int CH = BN / 8;
      const int mrow = m0 + wg * 64 + (warp & 3) * 16;
      for (int idx = lane; idx < 16 * CH; idx += 32) {
        const int rr = idx / CH, ch = idx % CH;
        if (n0 + ch * 8 < DFF_) {
          uint4 v = *reinterpret_cast<const uint4*>(st + rr * LDS + ch * 16);
          *reinterpret_cast<uint4*>(out + (size_t)(mrow + rr) * DFF_ + n0 + ch * 8) = v;
        }
      }
      TL(10 + MODE * 4, 0, tid == 128); TL(10 + MODE * 4, 1, tid == 128);
    } else {
      const int t = tid & 127;
      const int half = rank;
      {
        const uint32_t remote = mapa(smem_u32(sX), rank ^ 1);
#pragma unroll
        for (int i = 0; i < 8; i++) {
          asm volatile("st.shared::cluster.v4.f32 [%0], {%1, %2, %3, %4};" ::"r"(remote + ((wg * 8 + i) * 128 + t) * 16),
                       "f"(half ? acc[4 * i] : acc[32 + 4 * i]), "f"(half ? acc[4 * i + 1] : acc[32 + 4 * i + 1]),
                       "f"(half ? acc[4 * i + 2] : acc[32 + 4 * i + 2]), "f"(half ? acc[4 * i + 3] : acc[32 + 4 * i + 3])
                       : "memory");
        }
      }
      cluster_sync_all();
      TL(9 + MODE * 4, 1, tid == 128);
      constexpr int LDSF = 68;
      float* st = reinterpret_cast<float*>(sStage) + (warp - 4) * (16 * LDSF);
      {
        const int r = lane >> 2, cq = (lane & 3) * 2;
#pragma unroll
        for (int j = 0; j < 8; j++) {
          const float4 o = *reinterpret_cast<const float4*>(sX + ((wg * 8 + j) * 128 + t) * 16);
          float a0 = half ? acc[32 + 4 * j] : acc[4 * j], a1 = half ? acc[32 + 4 * j + 1] : acc[4 * j + 1];
          float a2 = half ? acc[32 + 4 * j + 2] : acc[4 * j + 2], a3 = half ? acc[32 + 4 * j + 3] : acc[4 * j + 3];
          float v0, v1, v2, v3;
          if (MODE == 0) {
            if (half == 0) { v0 = a0 - o.x; v1 = a1 - o.y; v2 = a2 - o.z; v3 = a3 - o.w; }
            else { v0 = o.x - a0; v1 = o.y - a1; v2 = o.z - a2; v3 = o.w - a3; }
          } else {
            v0 = a0 + o.x; v1 = a1 + o.y; v2 = a2 + o.z; v3 = a3 + o.w;
          }
          *reinterpret_cast<float2*>(st + r * LDSF + j * 8 + cq) = make_float2(v0, v1);
          *reinterpret_cast<float2*>(st + (r + 8) * LDSF + j * 8 + cq) = make_float2(v2, v3);
        }
      }
      __syncwarp();
      const float* gate = g_mod + (MODE == 0 ? 2 : 5) * D_;
      const int cbase = n0 + half * 64 + (lane & 7) * 8;
      float g[8];
#pragma unroll
      for (int j = 0; j < 8; j++) g[j] = gate[cbase + j];
      const int rloc = wg * 64 + (warp & 3) * 16;
      uint4 rv[4];
#pragma unroll
      for (int i = 0; i < 4; i++) rv[i] = *reinterpret_cast<const uint4*>(res + (size_t)(m0 + rloc + i * 4 + (lane >> 3)) * D_ + cbase);
      float xv[4][8];
#pragma unroll
      for (int i = 0; i < 4; i++) {
        const int rr = i * 4 + (lane >> 3);
        const float4 f0 = *reinterpret_cast<const float4*>(st + rr * LDSF + (lane & 7) * 8);
        const float4 f1 = *reinterpret_cast<const float4*>(st + rr * LDSF + (lane & 7) * 8 + 4);
        const uint32_t* ru = reinterpret_cast<const uint32_t*>(&rv[i]);
        float2 q;
        q = unpack_bf16(ru[0]); xv[i][0] = bf16_round(q.x + g[0] * f0.x); xv[i][1] = bf16_round(q.y + g[1] * f0.y);
        q = unpack_bf16(ru[1]); xv[i][2] = bf16_round(q.x + g[2] * f0.z); xv[i][3] = bf16_round(q.y + g[3] * f0.w);
        q = unpack_bf16(ru[2]); xv[i][4] = bf16_round(q.x + g[4] * f1.x); xv[i][5] = bf16_round(q.y + g[5] * f1.y);
        q = unpack_bf16(ru[3]); xv[i][6] = bf16_round(q.x + g[6] * f1.z); xv[i][7] = bf16_round(q.y + g[7] * f1.w);
        uint4 o;
        uint32_t* ou = reinterpret_cast<uint32_t*>(&o);
#pragma unroll
        for (int j = 0; j < 4; j++) ou[j] = pack_bf16(xv[i][2 * j], xv[i][2 * j + 1]);
        *reinterpret_cast<uint4*>(out + (size_t)(m0 + rloc + rr) * D_ + cbase) = o;
      }
      if (MODE == 0) {
        const float* scl = g_mod + 4 * D_;
        float sc[8];
#pragma unroll
        for (int j = 0; j < 8; j++) sc[j] = bf16_round(1.0f + scl[cbase + j]);
        float pm[4], pq[4];
#pragma unroll
        for (int i = 0; i < 4; i++) {
          uint4 o;
          uint32_t* ou = reinterpret_cast<uint32_t*>(&o);
#pragma unroll
          for (int j = 0; j < 4; j++) ou[j] = pack_bf16(xv[i][2 * j] * sc[2 * j], xv[i][2 * j + 1] * sc[2 * j + 1]);
          *reinterpret_cast<uint4*>(out2 + (size_t)(m0 + rloc + i * 4 + (lane >> 3)) * D_ + cbase) = o;
          float s = 0.f;
#pragma unroll
          for (int j = 0; j < 8; j++) s += xv[i][j];
          pm[i] = s;
        }
#pragma unroll
        for (int o = 1; o < 8; o <<= 1)
#pragma unroll
          for (int i = 0; i < 4; i++) pm[i] += __shfl_xor_sync(0xffffffffu, pm[i], o);
#pragma unroll
        for (int i = 0; i < 4; i++) {
          pm[i] *= (1.0f / 64.0f);
          float s = 0.f;
#pragma unroll
          for (int j = 0; j < 8; j++) { float d = xv[i][j] - pm[i]; s += d * d; }
          pq[i] = s;
        }
#pragma unroll
        for (int o = 1; o < 8; o <<= 1)
#pragma unroll
          for (int i = 0; i < 4; i++) pq[i] += __shfl_xor_sync(0xffffffffu, pq[i], o);
        if ((lane & 7) == 0) {
          const int blk = (n0 >> 6) + half;
#pragma unroll
          for (int i = 0; i < 4; i++) g_stat[(size_t)(m0 + rloc + i * 4 + (lane >> 3)) * 8 + blk] = make_float2(pm[i], pq[i]);
        }
      }
      TL(10 + MODE * 4, 0, tid == 128); TL(10 + MODE * 4, 1, tid == 128);
    }
  }
}

typedef CUresult (*PFN_encodeTiled_t)(CUtensorMap*, CUtensorMapDataType, cuuint32_t, void*, const cuuint64_t*,
                                      const cuuint64_t*, const cuuint32_t*, const cuuint32_t*, CUtensorMapInterleave,
                                      CUtensorMapSwizzle, CUtensorMapL2promotion, CUtensorMapFloatOOBfill);

CUtensorMap make_map(PFN_encodeTiled_t enc, const void* ptr, uint64_t inner, uint64_t outer, uint32_t box_inner,
                     uint32_t box_outer) {
  CUtensorMap m;
  cuuint64_t dims[2] = {inner, outer};
  cuuint64_t strides[1] = {inner * 2};
  cuuint32_t box[2] = {box_inner, box_outer};
  cuuint32_t es[2] = {1, 1};
  enc(&m, CU_TENSOR_MAP_DATA_TYPE_BFLOAT16, 2, const_cast<void*>(ptr), dims, strides, box, es,
      CU_TENSOR_MAP_INTERLEAVE_NONE, CU_TENSOR_MAP_SWIZZLE_128B, CU_TENSOR_MAP_L2_PROMOTION_L2_256B,
      CU_TENSOR_MAP_FLOAT_OOB_FILL_NONE);
  return m;
}

template <typename... KArgs, typename... Args>
void launch(void (*kern)(KArgs...), dim3 grid, dim3 block, size_t smem, bool pdl, Args... args) {
  cudaLaunchConfig_t cfg = {};
  cfg.gridDim = grid;
  cfg.blockDim = block;
  cfg.dynamicSmemBytes = smem;
  cfg.stream = cudaStreamPerThread;
  cudaLaunchAttribute at[1];
  at[0].id = cudaLaunchAttributeProgrammaticStreamSerialization;
  at[0].val.programmaticStreamSerializationAllowed = 1;
  cfg.attrs = at;
  cfg.numAttrs = pdl ? 1 : 0;
  cudaLaunchKernelEx(&cfg, kern, KArgs(args)...);
}

}

extern "C" void kernel_launch(void* const* d_in, const int* in_sizes, int n_in, void* d_out, int out_size) {
  const __nv_bfloat16* x = (const __nv_bfloat16*)d_in[0];
  const __nv_bfloat16* ws_re = (const __nv_bfloat16*)d_in[1];
  const __nv_bfloat16* ws_im = (const __nv_bfloat16*)d_in[2];
  const __nv_bfloat16* wd_re = (const __nv_bfloat16*)d_in[3];
  const __nv_bfloat16* wd_im = (const __nv_bfloat16*)d_in[4];
  const __nv_bfloat16* w1 = (const __nv_bfloat16*)d_in[6];
  const __nv_bfloat16* w2 = (const __nv_bfloat16*)d_in[7];
  const __nv_bfloat16* c = (const __nv_bfloat16*)d_in[8];
  const __nv_bfloat16* w_mod = (const __nv_bfloat16*)d_in[9];
  __nv_bfloat16* out = (__nv_bfloat16*)d_out;

  void* fn = nullptr;
  cudaDriverEntryPointQueryResult qres;
  cudaGetDriverEntryPoint("cuTensorMapEncodeTiled", &fn, cudaEnableDefault, &qres);
  PFN_encodeTiled_t enc = (PFN_encodeTiled_t)fn;

  void *p_ab, *p_x1, *p_h1, *p_x1s;
  cudaGetSymbolAddress(&p_ab, g_ab);
  cudaGetSymbolAddress(&p_x1, g_x1);
  cudaGetSymbolAddress(&p_h1, g_h1);
  cudaGetSymbolAddress(&p_x1s, g_x1s);

  const CUtensorMap m_wd_re = make_map(enc, wd_re, D_, D_, 64, 128);
  const CUtensorMap m_wd_im = make_map(enc, wd_im, D_, D_, 64, 128);
  const CUtensorMap m_ws_re = make_map(enc, ws_re, S_, S_, 64, 128);
  const CUtensorMap m_ws_im = make_map(enc, ws_im, S_, S_, 64, 128);
  const CUtensorMap m_ab = make_map(enc, p_ab, 2 * D_, S_, 64, 64);
  const CUtensorMap m_x1s = make_map(enc, p_x1s, D_, S_, 64, 128);
  const CUtensorMap m_w1 = make_map(enc, w1, DFF_, D_, 64, 32);
  const CUtensorMap m_h1 = make_map(enc, p_h1, DFF_, S_, 64, 128);
  const CUtensorMap m_w2 = make_map(enc, w2, D_, DFF_, 64, 64);

  constexpr int SM_K1 = G1_A_BYTES + G1_STAGES * G1_STAGE_BYTES + 256;
  cudaFuncSetAttribute(k_gemm1, cudaFuncAttributeMaxDynamicSharedMemorySize, SM_K1);
  cudaFuncSetAttribute(k_gemm<0>, cudaFuncAttributeMaxDynamicSharedMemorySize, g_smem_bytes<0>());
  cudaFuncSetAttribute(k_gemm<1>, cudaFuncAttributeMaxDynamicSharedMemorySize, g_smem_bytes<1>());
  cudaFuncSetAttribute(k_gemm<2>, cudaFuncAttributeMaxDynamicSharedMemorySize, g_smem_bytes<2>());

  launch(k_mod, dim3(48), dim3(256), 0, false, c, w_mod);
  launch(k_gemm1, dim3(132), dim3(384), SM_K1, true, m_wd_re, m_wd_im, x, w1, (__nv_bfloat16*)p_ab);
  launch(k_gemm<0>, dim3(8, 16), dim3(384), g_smem_bytes<0>(), true, m_ws_re, m_ws_im, m_ab, x, (__nv_bfloat16*)p_x1,
         (__nv_bfloat16*)p_x1s);
  launch(k_gemm<1>, dim3(16, 8), dim3(384), g_smem_bytes<1>(), true, m_x1s, m_x1s, m_w1, (const __nv_bfloat16*)nullptr,
         (__nv_bfloat16*)p_h1, (__nv_bfloat16*)nullptr);
  launch(k_gemm<2>, dim3(8, 16), dim3(384), g_smem_bytes<2>(), true, m_h1, m_h1, m_w2, (const __nv_bfloat16*)p_x1, out,
         (__nv_bfloat16*)nullptr);
}
```

```cpp
#include <cuda_runtime.h>
#include <cuda_bf16.h>
#include <cuda.h>
#include <stdint.h>

namespace {

constexpr int S_ = 2048, D_ = 512, DFF_ = 1376;

__device__ __align__(1024) float          g_mod[6 * D_];
__device__ __align__(1024) float          g_uv[2 * 1408];
__device__ __align__(1024) float2         g_stat[S_ * 8];
__device__ __align__(1024) __nv_bfloat16  g_ab[S_ * 2 * D_];
__device__ __align__(1024) __nv_bfloat16  g_x1[S_ * D_];
__device__ __align__(1024) __nv_bfloat16  g_x1s[S_ * D_];
__device__ __align__(1024) __nv_bfloat16  g_h1[S_ * DFF_];

#define TL(slot, which, cond)

__device__ __forceinline__ uint32_t smem_u32(const void* p) { return (uint32_t)__cvta_generic_to_shared(p); }

__device__ __forceinline__ void mbar_init(uint32_t bar, uint32_t count) {
  asm volatile("mbarrier.init.shared::cta.b64 [%0], %1;" ::"r"(bar), "r"(count) : "memory");
}
__device__ __forceinline__ void mbar_expect_tx(uint32_t bar, uint32_t bytes) {
  asm volatile("mbarrier.arrive.expect_tx.shared::cta.b64 _, [%0], %1;" ::"r"(bar), "r"(bytes) : "memory");
}
__device__ __forceinline__ void mbar_arrive(uint32_t bar) {
  asm volatile("mbarrier.arrive.shared::cta.b64 _, [%0];" ::"r"(bar) : "memory");
}
__device__ __forceinline__ uint32_t mapa(uint32_t addr, uint32_t rank) {
  uint32_t r;
  asm volatile("mapa.shared::cluster.u32 %0, %1, %2;" : "=r"(r) : "r"(addr), "r"(rank));
  return r;
}
__device__ __forceinline__ void mbar_arrive_remote(uint32_t bar, uint32_t rank) {
  asm volatile("mbarrier.arrive.release.cluster.shared::cluster.b64 _, [%0];" ::"r"(mapa(bar, rank)) : "memory");
}
__device__ __forceinline__ bool mbar_try_wait(uint32_t bar, uint32_t parity) {
  uint32_t ok;
  asm volatile(
      "{\n.reg .pred p;\n"
      "mbarrier.try_wait.parity.shared::cta.b64 p, [%1], %2;\n"
      "selp.u32 %0, 1, 0, p;\n}\n"
      : "=r"(ok)
      : "r"(bar), "r"(parity)
      : "memory");
  return ok != 0;
}
__device__ __forceinline__ void mbar_wait(uint32_t bar, uint32_t parity) {
  uint32_t spins = 0;
  while (!mbar_try_wait(bar, parity)) {
    if (++spins > (1u << 24)) __trap();
  }
}
__device__ __forceinline__ void tma_load_2d(uint32_t dst, const CUtensorMap* map, int c0, int c1, uint32_t bar) {
  asm volatile(
      "cp.async.bulk.tensor.2d.shared::cluster.global.mbarrier::complete_tx::bytes [%0], [%1, {%3, %4}], [%2];"
      ::"r"(dst), "l"(map), "r"(bar), "r"(c0), "r"(c1)
      : "memory");
}
__device__ __forceinline__ void tma_load_2d_mc(uint32_t dst, const CUtensorMap* map, int c0, int c1, uint32_t bar,
                                               uint16_t mask) {
  asm volatile(
      "cp.async.bulk.tensor.2d.shared::cluster.global.mbarrier::complete_tx::bytes.multicast::cluster [%0], [%1, {%3, %4}], [%2], %5;"
      ::"r"(dst), "l"(map), "r"(bar), "r"(c0), "r"(c1), "h"(mask)
      : "memory");
}
__device__ __forceinline__ void wgmma_fence() { asm volatile("wgmma.fence.sync.aligned;" ::: "memory"); }
__device__ __forceinline__ void wgmma_commit() { asm volatile("wgmma.commit_group.sync.aligned;" ::: "memory"); }
template <int N>
__device__ __forceinline__ void wgmma_wait() { asm volatile("wgmma.wait_group.sync.aligned %0;" ::"n"(N) : "memory"); }
__device__ __forceinline__ void fence_proxy_async() { asm volatile("fence.proxy.async.shared::cta;" ::: "memory"); }
__device__ __forceinline__ void named_bar_sync(int id, int nthreads) {
  asm volatile("bar.sync %0, %1;" ::"r"(id), "r"(nthreads) : "memory");
}
__device__ __forceinline__ void griddep_wait() { asm volatile("griddepcontrol.wait;" ::: "memory"); }
__device__ __forceinline__ void griddep_launch() { asm volatile("griddepcontrol.launch_dependents;" ::: "memory"); }
__device__ __forceinline__ void cluster_sync_all() {
  asm volatile("barrier.cluster.arrive.release.aligned;\nbarrier.cluster.wait.acquire.aligned;" ::: "memory");
}

__device__ __forceinline__ uint64_t desc_sw128(uint32_t addr, uint32_t lbo_bytes, uint32_t sbo_bytes) {
  uint64_t d = 0;
  d |= (uint64_t)((addr & 0x3FFFF) >> 4);
  d |= (uint64_t)((lbo_bytes & 0x3FFFF) >> 4) << 16;
  d |= (uint64_t)((sbo_bytes & 0x3FFFF) >> 4) << 32;
  d |= (uint64_t)1 << 62;
  return d;
}

template <int TNSPB, int SCALEA>
__device__ __forceinline__ void wgmma_n128(float (&d)[64], uint64_t da, uint64_t db, int scaleD) {
  asm volatile("{\n.reg .pred p;\nsetp.ne.b32 p, %66, 0;\n"
    "wgmma.mma_async.sync.aligned.m64n128k16.f32.bf16.bf16 {%0, %1, %2, %3, %4, %5, %6, %7, %8, %9, %10, %11, %12, %13, %14, %15, %16, %17, %18, %19, %20, %21, %22, %23, %24, %25, %26, %27, %28, %29, %30, %31, %32, %33, %34, %35, %36, %37, %38, %39, %40, %41, %42, %43, %44, %45, %46, %47, %48, %49, %50, %51, %52, %53, %54, %55, %56, %57, %58, %59, %60, %61, %62, %63}, %64, %65, p, %68, 1, 0, %67;\n}\n"
    : "+f"(d[0]), "+f"(d[1]), "+f"(d[2]), "+f"(d[3]), "+f"(d[4]), "+f"(d[5]), "+f"(d[6]), "+f"(d[7]), "+f"(d[8]), "+f"(d[9]), "+f"(d[10]), "+f"(d[11]), "+f"(d[12]), "+f"(d[13]), "+f"(d[14]), "+f"(d[15]), "+f"(d[16]), "+f"(d[17]), "+f"(d[18]), "+f"(d[19]), "+f"(d[20]), "+f"(d[21]), "+f"(d[22]), "+f"(d[23]), "+f"(d[24]), "+f"(d[25]), "+f"(d[26]), "+f"(d[27]), "+f"(d[28]), "+f"(d[29]), "+f"(d[30]), "+f"(d[31]), "+f"(d[32]), "+f"(d[33]), "+f"(d[34]), "+f"(d[35]), "+f"(d[36]), "+f"(d[37]), "+f"(d[38]), "+f"(d[39]), "+f"(d[40]), "+f"(d[41]), "+f"(d[42]), "+f"(d[43]), "+f"(d[44]), "+f"(d[45]), "+f"(d[46]), "+f"(d[47]), "+f"(d[48]), "+f"(d[49]), "+f"(d[50]), "+f"(d[51]), "+f"(d[52]), "+f"(d[53]), "+f"(d[54]), "+f"(d[55]), "+f"(d[56]), "+f"(d[57]), "+f"(d[58]), "+f"(d[59]), "+f"(d[60]), "+f"(d[61]), "+f"(d[62]), "+f"(d[63])
    : "l"(da), "l"(db), "r"(scaleD), "n"(TNSPB), "n"(SCALEA));
}

template <int TNSPB, int SCALEA>
__device__ __forceinline__ void wgmma_n176(float (&d)[88], uint64_t da, uint64_t db, int scaleD) {
  asm volatile("{\n.reg .pred p;\nsetp.ne.b32 p, %90, 0;\n"
    "wgmma.mma_async.sync.aligned.m64n176k16.f32.bf16.bf16 {%0, %1, %2, %3, %4, %5, %6, %7, %8, %9, %10, %11, %12, %13, %14, %15, %16, %17, %18, %19, %20, %21, %22, %23, %24, %25, %26, %27, %28, %29, %30, %31, %32, %33, %34, %35, %36, %37, %38, %39, %40, %41, %42, %43, %44, %45, %46, %47, %48, %49, %50, %51, %52, %53, %54, %55, %56, %57, %58, %59, %60, %61, %62, %63, %64, %65, %66, %67, %68, %69, %70, %71, %72, %73, %74, %75, %76, %77, %78, %79, %80, %81, %82, %83, %84, %85, %86, %87}, %88, %89, p, %92, 1, 0, %91;\n}\n"
    : "+f"(d[0]), "+f"(d[1]), "+f"(d[2]), "+f"(d[3]), "+f"(d[4]), "+f"(d[5]), "+f"(d[6]), "+f"(d[7]), "+f"(d[8]), "+f"(d[9]), "+f"(d[10]), "+f"(d[11]), "+f"(d[12]), "+f"(d[13]), "+f"(d[14]), "+f"(d[15]), "+f"(d[16]), "+f"(d[17]), "+f"(d[18]), "+f"(d[19]), "+f"(d[20]), "+f"(d[21]), "+f"(d[22]), "+f"(d[23]), "+f"(d[24]), "+f"(d[25]), "+f"(d[26]), "+f"(d[27]), "+f"(d[28]), "+f"(d[29]), "+f"(d[30]), "+f"(d[31]), "+f"(d[32]), "+f"(d[33]), "+f"(d[34]), "+f"(d[35]), "+f"(d[36]), "+f"(d[37]), "+f"(d[38]), "+f"(d[39]), "+f"(d[40]), "+f"(d[41]), "+f"(d[42]), "+f"(d[43]), "+f"(d[44]), "+f"(d[45]), "+f"(d[46]), "+f"(d[47]), "+f"(d[48]), "+f"(d[49]), "+f"(d[50]), "+f"(d[51]), "+f"(d[52]), "+f"(d[53]), "+f"(d[54]), "+f"(d[55]), "+f"(d[56]), "+f"(d[57]), "+f"(d[58]), "+f"(d[59]), "+f"(d[60]), "+f"(d[61]), "+f"(d[62]), "+f"(d[63]), "+f"(d[64]), "+f"(d[65]), "+f"(d[66]), "+f"(d[67]), "+f"(d[68]), "+f"(d[69]), "+f"(d[70]), "+f"(d[71]), "+f"(d[72]), "+f"(d[73]), "+f"(d[74]), "+f"(d[75]), "+f"(d[76]), "+f"(d[77]), "+f"(d[78]), "+f"(d[79]), "+f"(d[80]), "+f"(d[81]), "+f"(d[82]), "+f"(d[83]), "+f"(d[84]), "+f"(d[85]), "+f"(d[86]), "+f"(d[87])
    : "l"(da), "l"(db), "r"(scaleD), "n"(TNSPB), "n"(SCALEA));
}

__device__ __forceinline__ float bf16_round(float v) { return __bfloat162float(__float2bfloat16(v)); }
__device__ __forceinline__ uint32_t pack_bf16(float lo, float hi) {
  __nv_bfloat162 t = __floats2bfloat162_rn(lo, hi);
  return *reinterpret_cast<uint32_t*>(&t);
}
__device__ __forceinline__ float2 unpack_bf16(uint32_t u) {
  __nv_bfloat162 t = *reinterpret_cast<__nv_bfloat162*>(&u);
  return __bfloat1622float2(t);
}

__global__ void __launch_bounds__(256) k_mod(const __nv_bfloat16* __restrict__ c, const __nv_bfloat16* __restrict__ w_mod) {
  __shared__ float red[32][65];
  __shared__ float sc[D_];
  TL(0, 0, threadIdx.x == 0);
  griddep_launch();
  const int tx = threadIdx.x & 7, ty = threadIdx.x >> 3;
  const int col = blockIdx.x * 64 + tx * 8;
  uint4 v[16];
#pragma unroll
  for (int r = 0; r < 16; r++) v[r] = __ldg(reinterpret_cast<const uint4*>(w_mod + (size_t)(ty * 16 + r) * (6 * D_) + col));
  for (int i = threadIdx.x; i < D_; i += 256) {
    float x = __bfloat162float(c[i]);
    sc[i] = bf16_round(x / (1.0f + __expf(-x)));
  }
  __syncthreads();
  float acc[8];
#pragma unroll
  for (int j = 0; j < 8; j++) acc[j] = 0.f;
#pragma unroll
  for (int r = 0; r < 16; r++) {
    float s = sc[ty * 16 + r];
    const uint32_t* u = reinterpret_cast<const uint32_t*>(&v[r]);
#pragma unroll
    for (int j = 0; j < 4; j++) {
      float2 f = unpack_bf16(u[j]);
      acc[2 * j] += s * f.x;
      acc[2 * j + 1] += s * f.y;
    }
  }
#pragma unroll
  for (int j = 0; j < 8; j++) red[ty][tx * 8 + j] = acc[j];
  __syncthreads();
  if (threadIdx.x < 64) {
    float s = 0.f;
#pragma unroll
    for (int r = 0; r < 32; r++) s += red[r][threadIdx.x];
    g_mod[blockIdx.x * 64 + threadIdx.x] = bf16_round(s);
  }
  TL(0, 1, threadIdx.x == 0);
}

constexpr int G1_A_BYTES = 128 * 512 * 2;
constexpr int G1_STAGES = 4;
constexpr int G1_STAGE_BYTES = 16384;

__global__ void __launch_bounds__(384, 1)
k_gemm1(const __grid_constant__ CUtensorMap mapB0, const __grid_constant__ CUtensorMap mapB1, const __grid_constant__ CUtensorMap mapX,
        const __nv_bfloat16* __restrict__ xin, const __nv_bfloat16* __restrict__ w1, __nv_bfloat16* __restrict__ out) {
  constexpr int KT = 8;
  extern __shared__ __align__(1024) uint8_t smem[];
  const int tid = threadIdx.x, warp = tid >> 5, lane = tid & 31;

  if (blockIdx.x >= 128) {
    griddep_wait();
    griddep_launch();
    float* sk = reinterpret_cast<float*>(smem);
    float* red = sk + 1024;
    for (int i = tid; i < D_; i += 384) {
      sk[i] = bf16_round(1.0f + g_mod[4 * D_ + i]);
      sk[D_ + i] = g_mod[3 * D_ + i];
    }
    __syncthreads();
    const int c0 = (blockIdx.x - 128) * 344;
    const int cg = tid % 43, kg = tid / 43;
    if (kg < 8) {
      float u[8], v[8];
#pragma unroll
      for (int j = 0; j < 8; j++) { u[j] = 0.f; v[j] = 0.f; }
#pragma unroll 16
      for (int r = 0; r < 64; r++) {
        const int k = kg * 64 + r;
        const uint4 w = __ldg(reinterpret_cast<const uint4*>(w1 + (size_t)k * DFF_ + c0 + cg * 8));
        const uint32_t* wu = reinterpret_cast<const uint32_t*>(&w);
        const float a = sk[k], b = sk[D_ + k];
#pragma unroll
        for (int j = 0; j < 4; j++) {
          float2 f = unpack_bf16(wu[j]);
          u[2 * j] += a * f.x; u[2 * j + 1] += a * f.y;
          v[2 * j] += b * f.x; v[2 * j + 1] += b * f.y;
        }
      }
#pragma unroll
      for (int j = 0; j < 8; j++) {
        red[(kg * 344 + cg * 8 + j) * 2] = u[j];
        red[(kg * 344 + cg * 8 + j) * 2 + 1] = v[j];
      }
    }
    __syncthreads();
    if (tid < 344) {
      float u = 0.f, v = 0.f;
#pragma unroll
      for (int g = 0; g < 8; g++) { u += red[(g * 344 + tid) * 2]; v += red[(g * 344 + tid) * 2 + 1]; }
      g_uv[2 * (c0 + tid)] = u;
      g_uv[2 * (c0 + tid) + 1] = v;
    }
    return;
  }

  uint8_t* sA = smem;
  uint8_t* sB = smem + G1_A_BYTES;
  uint64_t* bars = reinterpret_cast<uint64_t*>(smem + G1_A_BYTES + G1_STAGES * G1_STAGE_BYTES);
  const uint32_t full0 = smem_u32(bars), empty0 = smem_u32(bars + G1_STAGES);
  const int m0 = (blockIdx.x >> 3) * 128, n0 = (blockIdx.x & 7) * 128;
  TL(4, 0, tid == 0);
  const CUtensorMap* mapB = n0 >= 512 ? &mapB1 : &mapB0;
  const int nb = n0 & 511;

  if (tid == 0) {
    for (int s = 0; s < G1_STAGES; s++) { mbar_init(full0 + 8 * s, 1); mbar_init(empty0 + 8 * s, 8); }
    mbar_init(smem_u32(bars + 2 * G1_STAGES), 1);
    asm volatile("fence.mbarrier_init.release.cluster;" ::: "memory");
    fence_proxy_async();
  }
  __syncthreads();

  auto issue_b = [&](int kt, int s) {
    const uint32_t bar = full0 + 8 * s;
    mbar_expect_tx(bar, G1_STAGE_BYTES);
    tma_load_2d(smem_u32(sB + s * G1_STAGE_BYTES), mapB, kt * 64, nb, bar);
  };
  if (tid == 0) {
    for (int s = 0; s < G1_STAGES; s++) issue_b(s, s);
  }

  const uint32_t xbar = smem_u32(bars + 2 * G1_STAGES);
  if (tid == 0) {
    mbar_expect_tx(xbar, G1_A_BYTES);
#pragma unroll
    for (int kc = 0; kc < 8; kc++) tma_load_2d(smem_u32(sA + kc * 16384), &mapX, kc * 64, m0, xbar);
  }
  griddep_wait();
  TL(4, 1, tid == 0);
  griddep_launch();
  {
    float sc[16], sh[16];
#pragma unroll
    for (int h = 0; h < 2; h++)
#pragma unroll
      for (int j = 0; j < 8; j++) {
        sc[h * 8 + j] = bf16_round(1.0f + g_mod[D_ + h * 256 + lane * 8 + j]);
        sh[h * 8 + j] = g_mod[h * 256 + lane * 8 + j];
      }
    mbar_wait(xbar, 0);
    for (int base = warp * 4; base < 128; base += 48) {
      float f[4][16], s[4], q[4];
#pragma unroll
      for (int i = 0; i < 4; i++) {
        const int row = base + i;
        const uint4 v0 = *reinterpret_cast<const uint4*>(sA + (lane >> 3) * 16384 + row * 128 + (((lane & 7) ^ (row & 7)) << 4));
        const uint4 v1 = *reinterpret_cast<const uint4*>(sA + ((lane >> 3) + 4) * 16384 + row * 128 + (((lane & 7) ^ (row & 7)) << 4));
        const uint32_t* u0 = reinterpret_cast<const uint32_t*>(&v0);
        const uint32_t* u1 = reinterpret_cast<const uint32_t*>(&v1);
        s[i] = 0.f;
#pragma unroll
        for (int j = 0; j < 4; j++) {
          float2 a = unpack_bf16(u0[j]), b = unpack_bf16(u1[j]);
          f[i][2 * j] = a.x; f[i][2 * j + 1] = a.y; f[i][8 + 2 * j] = b.x; f[i][8 + 2 * j + 1] = b.y;
          s[i] += (a.x + a.y) + (b.x + b.y);
        }
      }
#pragma unroll
      for (int o = 16; o > 0; o >>= 1)
#pragma unroll
        for (int i = 0; i < 4; i++) s[i] += __shfl_xor_sync(0xffffffffu, s[i], o);
#pragma unroll
      for (int i = 0; i < 4; i++) {
        const float mean = s[i] * (1.0f / D_);
        q[i] = 0.f;
#pragma unroll
        for (int j = 0; j < 16; j++) { f[i][j] -= mean; q[i] += f[i][j] * f[i][j]; }
      }
#pragma unroll
      for (int o = 16; o > 0; o >>= 1)
#pragma unroll
        for (int i = 0; i < 4; i++) q[i] += __shfl_xor_sync(0xffffffffu, q[i], o);
#pragma unroll
      for (int i = 0; i < 4; i++) {
        const int row = base + i;
        const float rstd = rsqrtf(q[i] * (1.0f / D_) + 1e-5f);
        uint4 o0, o1;
        uint32_t* p0 = reinterpret_cast<uint32_t*>(&o0);
        uint32_t* p1 = reinterpret_cast<uint32_t*>(&o1);
#pragma unroll
        for (int j = 0; j < 4; j++) {
          p0[j] = pack_bf16(f[i][2 * j] * rstd * sc[2 * j] + sh[2 * j], f[i][2 * j + 1] * rstd * sc[2 * j + 1] + sh[2 * j + 1]);
          p1[j] = pack_bf16(f[i][8 + 2 * j] * rstd * sc[8 + 2 * j] + sh[8 + 2 * j],
                            f[i][8 + 2 * j + 1] * rstd * sc[8 + 2 * j + 1] + sh[8 + 2 * j + 1]);
        }
        *reinterpret_cast<uint4*>(sA + (lane >> 3) * 16384 + row * 128 + (((lane & 7) ^ (row & 7)) << 4)) = o0;
        *reinterpret_cast<uint4*>(sA + ((lane >> 3) + 4) * 16384 + row * 128 + (((lane & 7) ^ (row & 7)) << 4)) = o1;
      }
    }
  }
  fence_proxy_async();
  __syncthreads();
  TL(5, 0, tid == 0);

  if (warp < 4) {
    if (tid == 0) {
      for (int kt = G1_STAGES; kt < KT; kt++) {
        const int s = kt % G1_STAGES;
        mbar_wait(empty0 + 8 * s, ((kt / G1_STAGES) - 1) & 1);
        issue_b(kt, s);
      }
    }
  } else {
    const int wg = (warp >> 2) - 1;
    float acc[64];
#pragma unroll
    for (int i = 0; i < 64; i++) acc[i] = 0.f;
    const uint32_t a_base = smem_u32(sA) + wg * 8192;
    for (int kt = 0; kt < KT; kt++) {
      const int s = kt % G1_STAGES;
      mbar_wait(full0 + 8 * s, (kt / G1_STAGES) & 1);
      wgmma_fence();
      const uint32_t bs = smem_u32(sB + s * G1_STAGE_BYTES);
#pragma unroll
      for (int k = 0; k < 4; k++) {
        const uint64_t da = desc_sw128(a_base + kt * 16384 + k * 32, 16, 1024);
        const uint64_t db = desc_sw128(bs + k * 32, 16, 1024);
        wgmma_n128<0, 1>(acc, da, db, 1);
      }
      wgmma_commit();
      wgmma_wait<1>();
      if (kt > 0 && lane == 0) mbar_arrive(empty0 + 8 * ((kt - 1) % G1_STAGES));
    }
    wgmma_wait<0>();
    named_bar_sync(1, 256);
    TL(5, 1, tid == 128);
    constexpr int LDS = 128 * 2 + 16;
    uint8_t* st = sA + (warp - 4) * (16 * LDS);
    {
      const int r = lane >> 2, cq = (lane & 3) * 2;
#pragma unroll
      for (int j = 0; j < 16; j++) {
        *reinterpret_cast<uint32_t*>(st + r * LDS + (j * 8 + cq) * 2) = pack_bf16(acc[4 * j], acc[4 * j + 1]);
        *reinterpret_cast<uint32_t*>(st + (r + 8) * LDS + (j * 8 + cq) * 2) = pack_bf16(acc[4 * j + 2], acc[4 * j + 3]);
      }
    }
    __syncwarp();
    const int mrow = m0 + wg * 64 + (warp & 3) * 16;
#pragma unroll
    for (int i = 0; i < 8; i++) {
      const int r = i * 2 + (lane >> 4), ch = lane & 15;
      uint4 v = *reinterpret_cast<const uint4*>(st + r * LDS + ch * 16);
      *reinterpret_cast<uint4*>(out + (size_t)(mrow + r) * (2 * D_) + n0 + ch * 8) = v;
    }
    TL(6, 0, tid == 128); TL(6, 1, tid == 128);
  }
}

template <int MODE> struct GCfg;
template <> struct GCfg<0> { static constexpr int BN = 128, NBOX = 2, KT = 32, STAGES = 4; };
template <> struct GCfg<1> { static constexpr int BN = 176, NBOX = 3, KT = 8, STAGES = 4; };
template <> struct GCfg<2> { static constexpr int BN = 128, NBOX = 2, KT = 11, STAGES = 4; };

constexpr int G_XCH_BYTES = 32768;
template <int MODE> constexpr int g_smem_bytes() {
  return GCfg<MODE>::STAGES * (16384 + GCfg<MODE>::NBOX * 8192) + (MODE != 1 ? G_XCH_BYTES : 4096) + 256;
}

template <int MODE>
__global__ void __cluster_dims__(2, 1, 1) __launch_bounds__(384, 1)
k_gemm(const __grid_constant__ CUtensorMap mapA0, const __grid_constant__ CUtensorMap mapA1,
       const __grid_constant__ CUtensorMap mapB, const __nv_bfloat16* __restrict__ res,
       __nv_bfloat16* __restrict__ out, __nv_bfloat16* __restrict__ out2) {
  using C = GCfg<MODE>;
  constexpr int BN = C::BN, KT = C::KT, STAGES = C::STAGES;
  constexpr int STAGE_BYTES = 16384 + C::NBOX * 8192;
  constexpr bool MC = false;
  extern __shared__ __align__(1024) uint8_t smem[];
  uint8_t* sStage = smem;
  uint8_t* sX = smem + STAGES * STAGE_BYTES;
  uint64_t* bars = reinterpret_cast<uint64_t*>(sX + (MODE != 1 ? G_XCH_BYTES : 4096));
  const uint32_t full0 = smem_u32(bars), empty0 = smem_u32(bars + STAGES);

  const int tid = threadIdx.x, warp = tid >> 5, lane = tid & 31;
  const int rank = blockIdx.x & 1;
  int m0, n0;
  if (MODE == 1) { m0 = (blockIdx.y * 2 + rank) * 128; n0 = (blockIdx.x >> 1) * BN; }
  else { m0 = blockIdx.y * 128; n0 = (blockIdx.x >> 1) * BN; }
  TL(8 + MODE * 4, 0, tid == 0);

  if (tid == 0) {
    for (int s = 0; s < STAGES; s++) { mbar_init(full0 + 8 * s, 1); mbar_init(empty0 + 8 * s, MC ? 16 : 8); }
    asm volatile("fence.mbarrier_init.release.cluster;" ::: "memory");
    fence_proxy_async();
  }
  __syncthreads();
  if (MC) cluster_sync_all();
  griddep_wait();
  TL(8 + MODE * 4, 1, tid == 0);
  griddep_launch();

  if (warp < 4) {
    if (tid == 0) {
      const CUtensorMap* mapA = (MODE == 0 && rank) ? &mapA1 : &mapA0;
      const int kbase = (MODE == 2) ? rank * 11 * 64 : 0;
      const int nb = (MODE == 0) ? n0 + rank * 512 : n0;
      for (int kt = 0; kt < KT; kt++) {
        const int s = kt % STAGES;
        if (kt >= STAGES) mbar_wait(empty0 + 8 * s, ((kt / STAGES) - 1) & 1);
        const uint32_t bar = full0 + 8 * s;
        const uint32_t dst = smem_u32(sStage + s * STAGE_BYTES);
        mbar_expect_tx(bar, STAGE_BYTES);
        const int k0 = kbase + kt * 64;
        tma_load_2d(dst, mapA, k0, m0, bar);
#pragma unroll
        for (int j = 0; j < C::NBOX; j++) {
          if (MC) tma_load_2d_mc(dst + 16384 + j * 8192 + rank * 4096, &mapB, nb + j * 64, k0 + rank * 32, bar, (uint16_t)3);
          else tma_load_2d(dst + 16384 + j * 8192, &mapB, nb + j * 64, k0, bar);
        }
      }
    } else if (MODE == 1 && tid >= 32) {
      for (int row = tid - 32; row < 128; row += 96) {
        const float4* p = reinterpret_cast<const float4*>(g_stat + (size_t)(m0 + row) * 8);
        float mb[8], qb[8];
#pragma unroll
        for (int b = 0; b < 4; b++) { const float4 t4 = p[b]; mb[2 * b] = t4.x; qb[2 * b] = t4.y; mb[2 * b + 1] = t4.z; qb[2 * b + 1] = t4.w; }
        float mean = 0.f;
#pragma unroll
        for (int b = 0; b < 8; b++) mean += mb[b];
        mean *= 0.125f;
        float m2 = 0.f;
#pragma unroll
        for (int b = 0; b < 8; b++) { const float d = mb[b] - mean; m2 += qb[b] + 64.0f * d * d; }
        reinterpret_cast<float2*>(sX)[row] = make_float2(mean, rsqrtf(m2 * (1.0f / D_) + 1e-5f));
      }
    }
    __syncwarp();
    if (MODE == 1) named_bar_sync(2, 384);
    cluster_sync_all();
  } else {
    const int wg = (warp >> 2) - 1;
    float acc[BN / 2];
#pragma unroll
    for (int i = 0; i < BN / 2; i++) acc[i] = 0.f;
    for (int kt = 0; kt < KT; kt++) {
      const int s = kt % STAGES;
      mbar_wait(full0 + 8 * s, (kt / STAGES) & 1);
      wgmma_fence();
      const uint32_t as = smem_u32(sStage + s * STAGE_BYTES) + wg * 8192;
      const uint32_t bs = smem_u32(sStage + s * STAGE_BYTES) + 16384;
#pragma unroll
      for (int k = 0; k < 4; k++) {
        const uint64_t da = desc_sw128(as + k * 32, 16, 1024);
        const uint64_t db = desc_sw128(bs + k * 2048, 8192, 1024);
        if (BN == 128) wgmma_n128<1, 1>(*reinterpret_cast<float(*)[64]>(acc), da, db, 1);
        else wgmma_n176<1, 1>(*reinterpret_cast<float(*)[88]>(acc), da, db, 1);
      }
      wgmma_commit();
      wgmma_wait<1>();
      if (kt > 0) {
        if (MC) { if (lane < 2) mbar_arrive_remote(empty0 + 8 * ((kt - 1) % STAGES), lane); }
        else if (lane == 0) mbar_arrive(empty0 + 8 * ((kt - 1) % STAGES));
      }
    }
    wgmma_wait<0>();
    TL(9 + MODE * 4, 0, tid == 128);

    if (MODE == 1) {
      named_bar_sync(2, 384);
      const int r = lane >> 2, cq = (lane & 3) * 2;
      const int rl = wg * 64 + (warp & 3) * 16 + r;
      const float2 st0 = reinterpret_cast<const float2*>(sX)[rl], st1 = reinterpret_cast<const float2*>(sX)[rl + 8];
      cluster_sync_all();
      constexpr int LDS = BN * 2 + 16;
      uint8_t* st = sStage + (warp - 4) * (16 * LDS);
#pragma unroll
      for (int j = 0; j < BN / 8; j++) {
        const int col = n0 + j * 8 + cq;
        float4 uv = make_float4(0.f, 0.f, 0.f, 0.f);
        if (col < DFF_) uv = *reinterpret_cast<const float4*>(g_uv + 2 * col);
        const float v0 = fmaxf(st0.y * (acc[4 * j] - st0.x * uv.x) + uv.y, 0.f);
        const float v1 = fmaxf(st0.y * (acc[4 * j + 1] - st0.x * uv.z) + uv.w, 0.f);
        const float v2 = fmaxf(st1.y * (acc[4 * j + 2] - st1.x * uv.x) + uv.y, 0.f);
        const float v3 = fmaxf(st1.y * (acc[4 * j + 3] - st1.x * uv.z) + uv.w, 0.f);
        *reinterpret_cast<uint32_t*>(st + r * LDS + (j * 8 + cq) * 2) = pack_bf16(v0, v1);
        *reinterpret_cast<uint32_t*>(st + (r + 8) * LDS + (j * 8 + cq) * 2) = pack_bf16(v2, v3);
      }
      __syncwarp();
      constexpr int CH = BN / 8;
      const int mrow = m0 + wg * 64 + (warp & 3) * 16;
      for (int idx = lane; idx < 16 * CH; idx += 32) {
        const int rr = idx / CH, ch = idx % CH;
        if (n0 + ch * 8 < DFF_) {
          uint4 v = *reinterpret_cast<const uint4*>(st + rr * LDS + ch * 16);
          *reinterpret_cast<uint4*>(out + (size_t)(mrow + rr) * DFF_ + n0 + ch * 8) = v;
        }
      }
      TL(10 + MODE * 4, 0, tid == 128); TL(10 + MODE * 4, 1, tid == 128);
    } else {
      const int t = tid & 127;
      const int half = rank;
      {
        const uint32_t remote = mapa(smem_u32(sX), rank ^ 1);
#pragma unroll
        for (int i = 0; i < 8; i++) {
          asm volatile("st.shared::cluster.v4.f32 [%0], {%1, %2, %3, %4};" ::"r"(remote + ((wg * 8 + i) * 128 + t) * 16),
                       "f"(half ? acc[4 * i] : acc[32 + 4 * i]), "f"(half ? acc[4 * i + 1] : acc[32 + 4 * i + 1]),
                       "f"(half ? acc[4 * i + 2] : acc[32 + 4 * i + 2]), "f"(half ? acc[4 * i + 3] : acc[32 + 4 * i + 3])
                       : "memory");
        }
      }
      cluster_sync_all();
      TL(9 + MODE * 4, 1, tid == 128);
      constexpr int LDSF = 68;
      float* st = reinterpret_cast<float*>(sStage) + (warp - 4) * (16 * LDSF);
      {
        const int r = lane >> 2, cq = (lane & 3) * 2;
#pragma unroll
        for (int j = 0; j < 8; j++) {
          const float4 o = *reinterpret_cast<const float4*>(sX + ((wg * 8 + j) * 128 + t) * 16);
          float a0 = half ? acc[32 + 4 * j] : acc[4 * j], a1 = half ? acc[32 + 4 * j + 1] : acc[4 * j + 1];
          float a2 = half ? acc[32 + 4 * j + 2] : acc[4 * j + 2], a3 = half ? acc[32 + 4 * j + 3] : acc[4 * j + 3];
          float v0, v1, v2, v3;
          if (MODE == 0) {
            if (half == 0) { v0 = a0 - o.x; v1 = a1 - o.y; v2 = a2 - o.z; v3 = a3 - o.w; }
            else { v0 = o.x - a0; v1 = o.y - a1; v2 = o.z - a2; v3 = o.w - a3; }
          } else {
            v0 = a0 + o.x; v1 = a1 + o.y; v2 = a2 + o.z; v3 = a3 + o.w;
          }
          *reinterpret_cast<float2*>(st + r * LDSF + j * 8 + cq) = make_float2(v0, v1);
          *reinterpret_cast<float2*>(st + (r + 8) * LDSF + j * 8 + cq) = make_float2(v2, v3);
        }
      }
      __syncwarp();
      const float* gate = g_mod + (MODE == 0 ? 2 : 5) * D_;
      const int cbase = n0 + half * 64 + (lane & 7) * 8;
      float g[8];
#pragma unroll
      for (int j = 0; j < 8; j++) g[j] = gate[cbase + j];
      const int rloc = wg * 64 + (warp & 3) * 16;
      uint4 rv[4];
#pragma unroll
      for (int i = 0; i < 4; i++) rv[i] = *reinterpret_cast<const uint4*>(res + (size_t)(m0 + rloc + i * 4 + (lane >> 3)) * D_ + cbase);
      float xv[4][8];
#pragma unroll
      for (int i = 0; i < 4; i++) {
        const int rr = i * 4 + (lane >> 3);
        const float4 f0 = *reinterpret_cast<const float4*>(st + rr * LDSF + (lane & 7) * 8);
        const float4 f1 = *reinterpret_cast<const float4*>(st + rr * LDSF + (lane & 7) * 8 + 4);
        const uint32_t* ru = reinterpret_cast<const uint32_t*>(&rv[i]);
        float2 q;
        q = unpack_bf16(ru[0]); xv[i][0] = bf16_round(q.x + g[0] * f0.x); xv[i][1] = bf16_round(q.y + g[1] * f0.y);
        q = unpack_bf16(ru[1]); xv[i][2] = bf16_round(q.x + g[2] * f0.z); xv[i][3] = bf16_round(q.y + g[3] * f0.w);
        q = unpack_bf16(ru[2]); xv[i][4] = bf16_round(q.x + g[4] * f1.x); xv[i][5] = bf16_round(q.y + g[5] * f1.y);
        q = unpack_bf16(ru[3]); xv[i][6] = bf16_round(q.x + g[6] * f1.z); xv[i][7] = bf16_round(q.y + g[7] * f1.w);
        uint4 o;
        uint32_t* ou = reinterpret_cast<uint32_t*>(&o);
#pragma unroll
        for (int j = 0; j < 4; j++) ou[j] = pack_bf16(xv[i][2 * j], xv[i][2 * j + 1]);
        *reinterpret_cast<uint4*>(out + (size_t)(m0 + rloc + rr) * D_ + cbase) = o;
      }
      if (MODE == 0) {
        const float* scl = g_mod + 4 * D_;
        float sc[8];
#pragma unroll
        for (int j = 0; j < 8; j++) sc[j] = bf16_round(1.0f + scl[cbase + j]);
        float pm[4], pq[4];
#pragma unroll
        for (int i = 0; i < 4; i++) {
          uint4 o;
          uint32_t* ou = reinterpret_cast<uint32_t*>(&o);
#pragma unroll
          for (int j = 0; j < 4; j++) ou[j] = pack_bf16(xv[i][2 * j] * sc[2 * j], xv[i][2 * j + 1] * sc[2 * j + 1]);
          *reinterpret_cast<uint4*>(out2 + (size_t)(m0 + rloc + i * 4 + (lane >> 3)) * D_ + cbase) = o;
          float s = 0.f;
#pragma unroll
          for (int j = 0; j < 8; j++) s += xv[i][j];
          pm[i] = s;
        }
#pragma unroll
        for (int o = 1; o < 8; o <<= 1)
#pragma unroll
          for (int i = 0; i < 4; i++) pm[i] += __shfl_xor_sync(0xffffffffu, pm[i], o);
#pragma unroll
        for (int i = 0; i < 4; i++) {
          pm[i] *= (1.0f / 64.0f);
          float s = 0.f;
#pragma unroll
          for (int j = 0; j < 8; j++) { float d = xv[i][j] - pm[i]; s += d * d; }
          pq[i] = s;
        }
#pragma unroll
        for (int o = 1; o < 8; o <<= 1)
#pragma unroll
          for (int i = 0; i < 4; i++) pq[i] += __shfl_xor_sync(0xffffffffu, pq[i], o);
        if ((lane & 7) == 0) {
          const int blk = (n0 >> 6) + half;
#pragma unroll
          for (int i = 0; i < 4; i++) g_stat[(size_t)(m0 + rloc + i * 4 + (lane >> 3)) * 8 + blk] = make_float2(pm[i], pq[i]);
        }
      }
      TL(10 + MODE * 4, 0, tid == 128); TL(10 + MODE * 4, 1, tid == 128);
    }
  }
}

typedef CUresult (*PFN_encodeTiled_t)(CUtensorMap*, CUtensorMapDataType, cuuint32_t, void*, const cuuint64_t*,
                                      const cuuint64_t*, const cuuint32_t*, const cuuint32_t*, CUtensorMapInterleave,
                                      CUtensorMapSwizzle, CUtensorMapL2promotion, CUtensorMapFloatOOBfill);

CUtensorMap make_map(PFN_encodeTiled_t enc, const void* ptr, uint64_t inner, uint64_t outer, uint32_t box_inner,
                     uint32_t box_outer) {
  CUtensorMap m;
  cuuint64_t dims[2] = {inner, outer};
  cuuint64_t strides[1] = {inner * 2};
  cuuint32_t box[2] = {box_inner, box_outer};
  cuuint32_t es[2] = {1, 1};
  enc(&m, CU_TENSOR_MAP_DATA_TYPE_BFLOAT16, 2, const_cast<void*>(ptr), dims, strides, box, es,
      CU_TENSOR_MAP_INTERLEAVE_NONE, CU_TENSOR_MAP_SWIZZLE_128B, CU_TENSOR_MAP_L2_PROMOTION_L2_256B,
      CU_TENSOR_MAP_FLOAT_OOB_FILL_NONE);
  return m;
}

template <typename... KArgs, typename... Args>
void launch(void (*kern)(KArgs...), dim3 grid, dim3 block, size_t smem, bool pdl, Args... args) {
  cudaLaunchConfig_t cfg = {};
  cfg.gridDim = grid;
  cfg.blockDim = block;
  cfg.dynamicSmemBytes = smem;
  cfg.stream = cudaStreamPerThread;
  cudaLaunchAttribute at[1];
  at[0].id = cudaLaunchAttributeProgrammaticStreamSerialization;
  at[0].val.programmaticStreamSerializationAllowed = 1;
  cfg.attrs = at;
  cfg.numAttrs = pdl ? 1 : 0;
  cudaLaunchKernelEx(&cfg, kern, KArgs(args)...);
}

}

extern "C" void kernel_launch(void* const* d_in, const int* in_sizes, int n_in, void* d_out, int out_size) {
  const __nv_bfloat16* x = (const __nv_bfloat16*)d_in[0];
  const __nv_bfloat16* ws_re = (const __nv_bfloat16*)d_in[1];
  const __nv_bfloat16* ws_im = (const __nv_bfloat16*)d_in[2];
  const __nv_bfloat16* wd_re = (const __nv_bfloat16*)d_in[3];
  const __nv_bfloat16* wd_im = (const __nv_bfloat16*)d_in[4];
  const __nv_bfloat16* w1 = (const __nv_bfloat16*)d_in[6];
  const __nv_bfloat16* w2 = (const __nv_bfloat16*)d_in[7];
  const __nv_bfloat16* c = (const __nv_bfloat16*)d_in[8];
  const __nv_bfloat16* w_mod = (const __nv_bfloat16*)d_in[9];
  __nv_bfloat16* out = (__nv_bfloat16*)d_out;

  void* fn = nullptr;
  cudaDriverEntryPointQueryResult qres;
  cudaGetDriverEntryPoint("cuTensorMapEncodeTiled", &fn, cudaEnableDefault, &qres);
  PFN_encodeTiled_t enc = (PFN_encodeTiled_t)fn;

  void *p_ab, *p_x1, *p_h1, *p_x1s;
  cudaGetSymbolAddress(&p_ab, g_ab);
  cudaGetSymbolAddress(&p_x1, g_x1);
  cudaGetSymbolAddress(&p_h1, g_h1);
  cudaGetSymbolAddress(&p_x1s, g_x1s);

  const CUtensorMap m_wd_re = make_map(enc, wd_re, D_, D_, 64, 128);
  const CUtensorMap m_x = make_map(enc, x, D_, S_, 64, 128);
  const CUtensorMap m_wd_im = make_map(enc, wd_im, D_, D_, 64, 128);
  const CUtensorMap m_ws_re = make_map(enc, ws_re, S_, S_, 64, 128);
  const CUtensorMap m_ws_im = make_map(enc, ws_im, S_, S_, 64, 128);
  const CUtensorMap m_ab = make_map(enc, p_ab, 2 * D_, S_, 64, 64);
  const CUtensorMap m_x1s = make_map(enc, p_x1s, D_, S_, 64, 128);
  const CUtensorMap m_w1 = make_map(enc, w1, DFF_, D_, 64, 64);
  const CUtensorMap m_h1 = make_map(enc, p_h1, DFF_, S_, 64, 128);
  const CUtensorMap m_w2 = make_map(enc, w2, D_, DFF_, 64, 64);

  constexpr int SM_K1 = G1_A_BYTES + G1_STAGES * G1_STAGE_BYTES + 256;
  cudaFuncSetAttribute(k_gemm1, cudaFuncAttributeMaxDynamicSharedMemorySize, SM_K1);
  cudaFuncSetAttribute(k_gemm<0>, cudaFuncAttributeMaxDynamicSharedMemorySize, g_smem_bytes<0>());
  cudaFuncSetAttribute(k_gemm<1>, cudaFuncAttributeMaxDynamicSharedMemorySize, g_smem_bytes<1>());
  cudaFuncSetAttribute(k_gemm<2>, cudaFuncAttributeMaxDynamicSharedMemorySize, g_smem_bytes<2>());

  launch(k_mod, dim3(48), dim3(256), 0, false, c, w_mod);
  launch(k_gemm1, dim3(132), dim3(384), SM_K1, true, m_wd_re, m_wd_im, m_x, x, w1, (__nv_bfloat16*)p_ab);
  launch(k_gemm<0>, dim3(8, 16), dim3(384), g_smem_bytes<0>(), true, m_ws_re, m_ws_im, m_ab, x, (__nv_bfloat16*)p_x1,
         (__nv_bfloat16*)p_x1s);
  launch(k_gemm<1>, dim3(16, 8), dim3(384), g_smem_bytes<1>(), true, m_x1s, m_x1s, m_w1, (const __nv_bfloat16*)nullptr,
         (__nv_bfloat16*)p_h1, (__nv_bfloat16*)nullptr);
  launch(k_gemm<2>, dim3(8, 16), dim3(384), g_smem_bytes<2>(), true, m_h1, m_h1, m_w2, (const __nv_bfloat16*)p_x1, out,
         (__nv_bfloat16*)nullptr);
}
```
